```python
import torch

def _softmax(x, axis=-1):
    return torch.softmax(x, dim=axis)

def _gelu(x):
    return torch.nn.functional.gelu(x, approximate='tanh')

def _silu(x):
    return torch.nn.functional.silu(x)

def _sigmoid(x):
    return torch.sigmoid(x)

def _layernorm(x, axis=-1, eps=1e-05):
    m = x.mean(dim=axis, keepdim=True)
    v = x.var(dim=axis, keepdim=True, unbiased=False)
    return (x - m) / torch.sqrt(v + eps)

def _scatter_add(tgt, idx, src, axis=0):
    return tgt.clone().index_add_(axis, idx, src)

def _segment_sum(src, seg, n):
    out = torch.zeros((n,) + src.shape[1:], dtype=src.dtype)
    return out.index_add_(0, seg, src)

def _pad(x, pw):
    flat = tuple((v for pair in reversed(pw) for v in pair))
    return torch.nn.functional.pad(x, flat)
kernel_name = 'adaLN_cond__sliding_block__glu_gated_bilinear__prompt'

def setup_inputs():

    _w = lambda a: (lambda t: t.to(torch.bfloat16) if t.is_floating_point() else t)(torch.as_tensor(a))

    def _A_setup():
        B, S, D = (1, 2048, 512)
        return {'x': _w((lambda *s: torch.randn(*s, dtype=torch.bfloat16) * 0.05)(B, S, D)), 'wqkv': _w((lambda *s: torch.randn(*s, dtype=torch.bfloat16) * 0.05)(D, 3 * D)), 'wo': _w((lambda *s: torch.randn(*s, dtype=torch.bfloat16) * 0.05)(D, D))}
    _A_in = _A_setup()

    def _B_setup():
        B, S, D, F = (1, 2048, 512, 1376)
        return {'x': _w((lambda *s: torch.randn(*s, dtype=torch.bfloat16) * 0.05)(B, S, D)), 'w_gate': _w((lambda *s: torch.randn(*s, dtype=torch.bfloat16) * 0.8)(D, F) * D ** (-0.5)), 'w_up': _w((lambda *s: torch.randn(*s, dtype=torch.bfloat16) * 0.8)(D, F) * D ** (-0.5)), 'w_down': _w((lambda *s: torch.randn(*s, dtype=torch.bfloat16) * 0.8)(F, D) * F ** (-0.5))}
    _B_in = _B_setup()
    return {'A_x': _A_in['x'], 'A_wqkv': _A_in['wqkv'], 'A_wo': _A_in['wo'], 'B_x': _B_in['x'], 'B_w_gate': _B_in['w_gate'], 'B_w_up': _B_in['w_up'], 'B_w_down': _B_in['w_down'], 'c': _w((lambda *s: torch.randn(*s, dtype=torch.bfloat16) * 0.1)(1, 512) * 8.0), 'w_mod': _w((lambda *s: torch.randn(*s, dtype=torch.bfloat16) * 0.1)(512, 6 * 512) * 512 ** (-0.5) * 8.0)}

def reference(A_x, A_wqkv, A_wo, B_x, B_w_gate, B_w_up, B_w_down, c, w_mod):

    def _A_ref(x, wqkv, wo):
        B, S, D = x.shape
        H = 32
        Dh = D // H
        W = 256
        qkv = (lambda x, *d: x.permute(*d))((x @ wqkv).reshape(B, S, 3, H, Dh), 2, 0, 3, 1, 4)
        q, k, v = (qkv[0], qkv[1], qkv[2])
        scores = torch.einsum('bhqd,bhkd->bhqk', q, k) * Dh ** (-0.5)
        idx = torch.arange(S)
        mask = (idx[:, None] - idx[None, :] >= 0) & (idx[:, None] - idx[None, :] < W)
        scores = torch.where(mask[None, None], scores, -1000000000.0)
        p = _softmax(scores, axis=-1)
        o = torch.einsum('bhqk,bhkd->bhqd', p, v)
        return (lambda x, *d: x.permute(*d))(o, 0, 2, 1, 3).reshape(B, S, D) @ wo

    def _B_ref(x, w_gate, w_up, w_down):
        g = torch.einsum('bsd,df->bsf', x, w_gate)
        u = torch.einsum('bsd,df->bsf', x, w_up)
        h = g * u
        return torch.einsum('bsf,fd->bsd', h, w_down)
    x = A_x
    mod = (_silu(c) @ w_mod).reshape(c.shape[0], 6, 1, -1)
    sa, ca, ga, sb, cb, gb = (mod[:, 0].clone(), mod[:, 1].clone(), mod[:, 2].clone(), mod[:, 3].clone(), mod[:, 4].clone(), mod[:, 5].clone())
    h = _layernorm(x, axis=-1) * (1 + ca) + sa
    x = x + ga * _A_ref(h, A_wqkv, A_wo)
    h = _layernorm(x, axis=-1) * (1 + cb) + sb
    x = x + gb * _B_ref(h, B_w_gate, B_w_up, B_w_down)
    return x
```

```cpp
#include <cuda_runtime.h>
#include <cuda_bf16.h>
#include <cuda.h>
#include <stdint.h>

namespace {

constexpr int NSTAGE = 13;
constexpr int STAGE_BYTES = 16384;
constexpr int KV_OFF = 7 * STAGE_BYTES;
constexpr int TAB1_OFF = NSTAGE * STAGE_BYTES;
constexpr int TAB2_OFF = TAB1_OFF + 2048;
constexpr int GA_OFF = TAB2_OFF + 2048;
constexpr int GB_OFF = GA_OFF + 256;
constexpr int RED_OFF = GB_OFF + 256;
constexpr int MISC_OFF = RED_OFF + 512;
constexpr int BAR_OFF = MISC_OFF + 64;
constexpr int B_FULL = 0, B_EMPTY = 13, B_KVW = 26, B_HALO = 30, B_EPOCH = 34, B_TAB2 = 35, NBAR = 36;
constexpr int SMEM_BYTES = BAR_OFF + NBAR * 8;

constexpr int SPIN_LIMIT = 1 << 22;
#define DIE() asm volatile("st.global.u32 [%0], %1;" ::"l"(0ull), "r"(0) : "memory")

__device__ uint4 g_kv[16 * 8 * 2048];
__device__ uint4 g_o[16 * 8 * 32 * 32];
__device__ uint4 g_x1[16 * 8 * 32 * 32];
__device__ uint4 g_st[16 * 8 * 8 * 8];
__device__ uint4 g_hh[16 * 8 * 8 * 11 * 32];
__device__ uint2 g_mod[1536];
__device__ uint4 g_kvflag[16 * 8 * 2];
__device__ unsigned g_epoch;
#define PROF(i) do {} while (0)

__device__ __forceinline__ uint32_t s2u(const void* p) { return (uint32_t)__cvta_generic_to_shared(p); }
__device__ __forceinline__ void mbar_init(uint32_t b, int c) {
    asm volatile("mbarrier.init.shared::cta.b64 [%0], %1;" ::"r"(b), "r"(c) : "memory");
}
__device__ __forceinline__ void mbar_expect(uint32_t b, uint32_t bytes) {
    asm volatile("mbarrier.arrive.expect_tx.shared::cta.b64 _, [%0], %1;" ::"r"(b), "r"(bytes) : "memory");
}
__device__ __forceinline__ void mbar_arrive(uint32_t b) {
    asm volatile("mbarrier.arrive.shared::cta.b64 _, [%0];" ::"r"(b) : "memory");
}
__device__ __forceinline__ void mbar_wait(uint32_t b, uint32_t ph) {
    asm volatile(
        "{\n.reg .pred p;\n.reg .u32 n;\n"
        "mbarrier.try_wait.parity.shared::cta.b64 p, [%0], %1;\n"
        "@p bra DONE_%=;\n"
        "mov.u32 n, 0;\n"
        "LOOP_%=:\n"
        "mbarrier.try_wait.parity.shared::cta.b64 p, [%0], %1;\n"
        "@p bra DONE_%=;\n"
        "add.u32 n, n, 1;\n"
        "setp.lt.u32 p, n, %2;\n"
        "@p bra LOOP_%=;\n"
        "st.global.u32 [%3], n;\n"
        "DONE_%=:\n}" ::"r"(b), "r"(ph), "n"(SPIN_LIMIT), "l"(0ull) : "memory");
}
__device__ __forceinline__ void bar_sync(int id, int n) { asm volatile("bar.sync %0, %1;" ::"r"(id), "r"(n) : "memory"); }
__device__ __forceinline__ void bar_arrive(int id, int n) { asm volatile("bar.arrive %0, %1;" ::"r"(id), "r"(n) : "memory"); }
__device__ __forceinline__ void fence_async_smem() { asm volatile("fence.proxy.async.shared::cta;" ::: "memory"); }
__device__ __forceinline__ void fence_async_all() { asm volatile("fence.proxy.async;" ::: "memory"); }

__device__ __forceinline__ void tma2d(uint32_t dst, const CUtensorMap* m, int c0, int c1, uint32_t bar) {
    asm volatile("cp.async.bulk.tensor.2d.shared::cluster.global.mbarrier::complete_tx::bytes [%0], [%1, {%3, %4}], [%2];"
                 ::"r"(dst), "l"(m), "r"(bar), "r"(c0), "r"(c1) : "memory");
}
__device__ __forceinline__ void tma5d(uint32_t dst, const CUtensorMap* m, int c0, int c4, uint32_t bar) {
    asm volatile("cp.async.bulk.tensor.5d.shared::cluster.global.mbarrier::complete_tx::bytes [%0], [%1, {%3, %5, %5, %5, %4}], [%2];"
                 ::"r"(dst), "l"(m), "r"(bar), "r"(c0), "r"(c4), "r"(0) : "memory");
}
__device__ __forceinline__ void bulk_g2s(uint32_t dst, const void* src, uint32_t bytes, uint32_t bar) {
    asm volatile("cp.async.bulk.shared::cluster.global.mbarrier::complete_tx::bytes [%0], [%1], %2, [%3];"
                 ::"r"(dst), "l"(src), "r"(bytes), "r"(bar) : "memory");
}
__device__ __forceinline__ void bulk_s2g(void* dst, uint32_t src, uint32_t bytes) {
    asm volatile("cp.async.bulk.global.shared::cta.bulk_group [%0], [%1], %2;" ::"l"(dst), "r"(src), "r"(bytes) : "memory");
}
__device__ __forceinline__ void prefetch_l2(const void* p, uint32_t bytes) {
    asm volatile("cp.async.bulk.prefetch.L2.global [%0], %1;" ::"l"(p), "r"(bytes) : "memory");
}
__device__ __forceinline__ uint4 ldg_nc(const void* p) {
    uint4 v;
    asm volatile("ld.global.nc.L1::no_allocate.v4.u32 {%0,%1,%2,%3}, [%4];" : "=r"(v.x), "=r"(v.y), "=r"(v.z), "=r"(v.w) : "l"(p));
    return v;
}
__device__ __forceinline__ uint4 ld_rlx(const void* p) {
    uint4 v;
    asm volatile("{\n.reg .b128 t;\n.reg .b64 a, b;\nld.relaxed.gpu.global.b128 t, [%4];\nmov.b128 {a, b}, t;\n"
                 "mov.b64 {%0,%1}, a;\nmov.b64 {%2,%3}, b;\n}"
                 : "=r"(v.x), "=r"(v.y), "=r"(v.z), "=r"(v.w) : "l"(p) : "memory");
    return v;
}
__device__ __forceinline__ void st_rlx(void* p, uint32_t x, uint32_t y, uint32_t z, uint32_t w) {
    asm volatile("{\n.reg .b128 t;\n.reg .b64 a, b;\nmov.b64 a, {%1,%2};\nmov.b64 b, {%3,%4};\nmov.b128 t, {a, b};\n"
                 "st.relaxed.gpu.global.b128 [%0], t;\n}" ::"l"(p), "r"(x), "r"(y), "r"(z), "r"(w) : "memory");
}
__device__ __forceinline__ uint32_t tagw(uint32_t x, uint32_t par) { return (x & ~1u) | par; }
template <int N, class F>
__device__ __forceinline__ void validate(uint4* v, const uint4* p, F off, uint32_t par) {
    uint32_t all1 = v[0].x, any1 = v[0].x;
#pragma unroll
    for (int i = 1; i < N; ++i) { all1 &= v[i].x; any1 |= v[i].x; }
    uint32_t bad = (par ? ~all1 : any1) & 1u;
    int it = 0;
#pragma unroll 1
    while (bad) {
#pragma unroll
        for (int i = 0; i < N; ++i) v[i] = ld_rlx(p + off(i));
        all1 = v[0].x; any1 = v[0].x;
#pragma unroll
        for (int i = 1; i < N; ++i) { all1 &= v[i].x; any1 |= v[i].x; }
        bad = (par ? ~all1 : any1) & 1u;
        if (++it > SPIN_LIMIT) { DIE(); break; }
    }
    __syncwarp();
}
__device__ __forceinline__ uint4 lds128(uint32_t a) {
    uint4 v;
    asm volatile("ld.shared.v4.u32 {%0,%1,%2,%3}, [%4];" : "=r"(v.x), "=r"(v.y), "=r"(v.z), "=r"(v.w) : "r"(a) : "memory");
    return v;
}
__device__ __forceinline__ void sts128(uint32_t a, uint32_t x, uint32_t y, uint32_t z, uint32_t w) {
    asm volatile("st.shared.v4.u32 [%0], {%1,%2,%3,%4};" ::"r"(a), "r"(x), "r"(y), "r"(z), "r"(w) : "memory");
}
__device__ __forceinline__ uint32_t pack2(float lo, float hi) {
    uint32_t d;
    asm("cvt.rn.bf16x2.f32 %0, %1, %2;" : "=r"(d) : "f"(hi), "f"(lo));
    return d;
}
__device__ __forceinline__ float bf_lo(uint32_t x) { return __uint_as_float(x << 16); }
__device__ __forceinline__ float bf_hi(uint32_t x) { return __uint_as_float(x & 0xffff0000u); }
__device__ __forceinline__ uint32_t hfma2(uint32_t a, uint32_t b, uint32_t c) {
    uint32_t d;
    asm("fma.rn.bf16x2 %0, %1, %2, %3;" : "=r"(d) : "r"(a), "r"(b), "r"(c));
    return d;
}
__device__ __forceinline__ uint32_t hmul2(uint32_t a, uint32_t b) {
    uint32_t d;
    asm("mul.rn.bf16x2 %0, %1, %2;" : "=r"(d) : "r"(a), "r"(b));
    return d;
}
__device__ __forceinline__ float ex2f(float x) {
    float y;
    asm("ex2.approx.ftz.f32 %0, %1;" : "=f"(y) : "f"(x));
    return y;
}
__device__ __forceinline__ uint32_t movmat(uint32_t a) {
    uint32_t d;
    asm volatile("movmatrix.sync.aligned.m8n8.trans.b16 %0, %1;" : "=r"(d) : "r"(a));
    return d;
}
__device__ __forceinline__ void mma16816(float& d0, float& d1, float& d2, float& d3, uint32_t a0, uint32_t a1, uint32_t a2,
                                         uint32_t a3, uint32_t b0, uint32_t b1, float c0, float c1, float c2, float c3) {
    asm("mma.sync.aligned.m16n8k16.row.col.f32.bf16.bf16.f32 {%0,%1,%2,%3}, {%4,%5,%6,%7}, {%8,%9}, {%10,%11,%12,%13};"
        : "=f"(d0), "=f"(d1), "=f"(d2), "=f"(d3)
        : "r"(a0), "r"(a1), "r"(a2), "r"(a3), "r"(b0), "r"(b1), "f"(c0), "f"(c1), "f"(c2), "f"(c3));
}
#define WG_FENCE() asm volatile("wgmma.fence.sync.aligned;" ::: "memory")
#define WG_COMMIT() asm volatile("wgmma.commit_group.sync.aligned;" ::: "memory")
#define WG_WAIT(n) asm volatile("wgmma.wait_group.sync.aligned %0;" ::"n"(n) : "memory")

__device__ __forceinline__ constexpr uint64_t bdesc(uint32_t addr) {
    return (uint64_t)(((addr & 0x3FFFFu) >> 4) | (512u << 16)) | ((uint64_t)(64u | (1u << 30)) << 32);
}

#define ACC8(d, o) "+f"(d[o]), "+f"(d[o + 1]), "+f"(d[o + 2]), "+f"(d[o + 3]), "+f"(d[o + 4]), "+f"(d[o + 5]), "+f"(d[o + 6]), "+f"(d[o + 7])
template <int SC>
__device__ __forceinline__ void wgmma128(float (&d)[64], const uint4& a, uint64_t db) {
    asm volatile(
        "wgmma.mma_async.sync.aligned.m64n128k16.f32.bf16.bf16 "
        "{%0,%1,%2,%3,%4,%5,%6,%7,%8,%9,%10,%11,%12,%13,%14,%15,%16,%17,%18,%19,%20,%21,%22,%23,%24,%25,%26,%27,%28,%29,%30,%31,"
        "%32,%33,%34,%35,%36,%37,%38,%39,%40,%41,%42,%43,%44,%45,%46,%47,%48,%49,%50,%51,%52,%53,%54,%55,%56,%57,%58,%59,%60,%61,%62,%63},"
        "{%64,%65,%66,%67}, %68, %69, 1, 1, 1;"
        : ACC8(d, 0), ACC8(d, 8), ACC8(d, 16), ACC8(d, 24), ACC8(d, 32), ACC8(d, 40), ACC8(d, 48), ACC8(d, 56)
        : "r"(a.x), "r"(a.y), "r"(a.z), "r"(a.w), "l"(db), "n"(SC));
}
template <int SC>
__device__ __forceinline__ void wgmma64(float (&d)[32], const uint4& a, uint64_t db) {
    asm volatile(
        "wgmma.mma_async.sync.aligned.m64n64k16.f32.bf16.bf16 "
        "{%0,%1,%2,%3,%4,%5,%6,%7,%8,%9,%10,%11,%12,%13,%14,%15,%16,%17,%18,%19,%20,%21,%22,%23,%24,%25,%26,%27,%28,%29,%30,%31},"
        "{%32,%33,%34,%35}, %36, %37, 1, 1, 1;"
        : ACC8(d, 0), ACC8(d, 8), ACC8(d, 16), ACC8(d, 24)
        : "r"(a.x), "r"(a.y), "r"(a.z), "r"(a.w), "l"(db), "n"(SC));
}
template <int SC>
__device__ __forceinline__ void wgmma48(float (&d)[24], const uint4& a, uint64_t db) {
    asm volatile(
        "wgmma.mma_async.sync.aligned.m64n48k16.f32.bf16.bf16 "
        "{%0,%1,%2,%3,%4,%5,%6,%7,%8,%9,%10,%11,%12,%13,%14,%15,%16,%17,%18,%19,%20,%21,%22,%23},"
        "{%24,%25,%26,%27}, %28, %29, 1, 1, 1;"
        : ACC8(d, 0), ACC8(d, 8), ACC8(d, 16)
        : "r"(a.x), "r"(a.y), "r"(a.z), "r"(a.w), "l"(db), "n"(SC));
}

__device__ __forceinline__ void ln_mod(uint4& a, uint4 cs, float rs0, float nm0, float rs1, float nm1) {
    a.x = hfma2(pack2(fmaf(bf_lo(a.x), rs0, nm0), fmaf(bf_hi(a.x), rs0, nm0)), cs.x, cs.z);
    a.y = hfma2(pack2(fmaf(bf_lo(a.y), rs1, nm1), fmaf(bf_hi(a.y), rs1, nm1)), cs.x, cs.z);
    a.z = hfma2(pack2(fmaf(bf_lo(a.z), rs0, nm0), fmaf(bf_hi(a.z), rs0, nm0)), cs.y, cs.w);
    a.w = hfma2(pack2(fmaf(bf_lo(a.w), rs1, nm1), fmaf(bf_hi(a.w), rs1, nm1)), cs.y, cs.w);
}
__device__ __forceinline__ float silu_bf(float c) {
    float s = c / (1.0f + __expf(-c));
    return __bfloat162float(__float2bfloat16(s));
}
__device__ __forceinline__ uint32_t one_plus(uint32_t v) { return pack2(1.0f + bf_lo(v), 1.0f + bf_hi(v)); }

__device__ __forceinline__ constexpr int wpos(int m) { return m % NSTAGE; }
__device__ __forceinline__ constexpr int wpar(int m) { return ((m % NSTAGE == 0 ? 0 : 1) + m / NSTAGE) & 1; }

__global__ void __launch_bounds__(384, 1)
fused_kernel(const __grid_constant__ CUtensorMap tmQKV, const __grid_constant__ CUtensorMap tmWo,
             const __grid_constant__ CUtensorMap tmG, const __grid_constant__ CUtensorMap tmU,
             const __grid_constant__ CUtensorMap tmD, const __nv_bfloat16* __restrict__ x,
             const __nv_bfloat16* __restrict__ wo, const __nv_bfloat16* __restrict__ wg, const __nv_bfloat16* __restrict__ wu,
             const __nv_bfloat16* __restrict__ wd, const __nv_bfloat16* __restrict__ cvec,
             const __nv_bfloat16* __restrict__ wmod, __nv_bfloat16* __restrict__ out) {
    extern __shared__ __align__(1024) unsigned char smem[];
    constexpr uint32_t sb = 1024;
    if (s2u(smem) != sb) { DIE(); return; }
    constexpr uint32_t bars = sb + BAR_OFF;
    const int bid = blockIdx.x;
    const int j = bid >> 3, r = bid & 7;
    const int lane = threadIdx.x & 31;
    const int warp = threadIdx.x >> 5;

    if (warp >= 8) {
        asm volatile("setmaxnreg.dec.sync.aligned.u32 40;");
        const int t2 = threadIdx.x - 256;
        volatile unsigned* s_epoch = (volatile unsigned*)(smem + MISC_OFF);
        float* red = (float*)(smem + RED_OFF);
        {
            uint4 wv[4];
#pragma unroll
            for (int i = 0; i < 4; ++i) wv[i] = ldg_nc(wmod + (size_t)(t2 * 4 + i) * 3072 + 8 * bid);
            uint2 cv = *(const uint2*)(cvec + t2 * 4);
            if (t2 == 32) {
                unsigned e;
                asm volatile("ld.relaxed.gpu.global.u32 %0, [%1];" : "=r"(e) : "l"(&g_epoch) : "memory");
                *s_epoch = e + 1;
            }
            if (t2 == 0) {
                for (int i = 0; i < NSTAGE; ++i) { mbar_init(bars + 8 * (B_FULL + i), 1); mbar_init(bars + 8 * (B_EMPTY + i), 8); }
                for (int i = 0; i < 4; ++i) { mbar_init(bars + 8 * (B_KVW + i), 8); mbar_init(bars + 8 * (B_HALO + i), 1); }
                mbar_init(bars + 8 * B_EPOCH, 1);
                mbar_init(bars + 8 * B_TAB2, 1);
                asm volatile("fence.mbarrier_init.release.cluster;" ::: "memory");
                fence_async_all();
#pragma unroll 1
                for (int kb = 0; kb < 8; ++kb) {
                    int pos = kb < 6 ? 7 + kb : kb - 5;
                    uint32_t fb = bars + 8 * (B_FULL + pos), dst = sb + pos * STAGE_BYTES;
                    mbar_expect(fb, STAGE_BYTES);
                    tma5d(dst, &tmQKV, 512 + 64 * r, 2 * kb, fb);
                    tma5d(dst + 8192, &tmQKV, 1024 + 64 * r, 2 * kb, fb);
                }
#pragma unroll 1
                for (int q = 0; q < 4; ++q) {
                    uint32_t fb = bars + 8 * (B_FULL + 3 + q), dst = sb + (3 + q) * STAGE_BYTES;
                    mbar_expect(fb, STAGE_BYTES);
                    tma5d(dst, &tmQKV, 64 * r, 4 * q, fb);
                    tma5d(dst + 8192, &tmQKV, 64 * r, 4 * q + 2, fb);
                }
            }
            __syncwarp();
            bar_arrive(0, 384);
            float s[4] = {silu_bf(bf_lo(cv.x)), silu_bf(bf_hi(cv.x)), silu_bf(bf_lo(cv.y)), silu_bf(bf_hi(cv.y))};
            float a[8];
#pragma unroll
            for (int k = 0; k < 8; ++k) a[k] = 0.f;
#pragma unroll
            for (int i = 0; i < 4; ++i) {
                a[0] = fmaf(s[i], bf_lo(wv[i].x), a[0]); a[1] = fmaf(s[i], bf_hi(wv[i].x), a[1]);
                a[2] = fmaf(s[i], bf_lo(wv[i].y), a[2]); a[3] = fmaf(s[i], bf_hi(wv[i].y), a[3]);
                a[4] = fmaf(s[i], bf_lo(wv[i].z), a[4]); a[5] = fmaf(s[i], bf_hi(wv[i].z), a[5]);
                a[6] = fmaf(s[i], bf_lo(wv[i].w), a[6]); a[7] = fmaf(s[i], bf_hi(wv[i].w), a[7]);
            }
            const bool u16 = lane & 16, u8 = lane & 8, u4 = lane & 4;
#pragma unroll
            for (int k = 0; k < 4; ++k) {
                float keep = u16 ? a[k + 4] : a[k], send = u16 ? a[k] : a[k + 4];
                a[k] = keep + __shfl_xor_sync(~0u, send, 16);
            }
#pragma unroll
            for (int k = 0; k < 2; ++k) {
                float keep = u8 ? a[k + 2] : a[k], send = u8 ? a[k] : a[k + 2];
                a[k] = keep + __shfl_xor_sync(~0u, send, 8);
            }
            {
                float keep = u4 ? a[1] : a[0], send = u4 ? a[0] : a[1];
                a[0] = keep + __shfl_xor_sync(~0u, send, 4);
            }
            a[0] += __shfl_xor_sync(~0u, a[0], 2);
            a[0] += __shfl_xor_sync(~0u, a[0], 1);
            if ((lane & 3) == 0) red[(warp - 8) * 8 + (lane >> 2)] = a[0];
            bar_sync(2, 128);
            if (t2 == 32) mbar_arrive(bars + 8 * B_EPOCH);
            if (t2 < 4) {
                float v0 = red[2 * t2] + red[8 + 2 * t2] + red[16 + 2 * t2] + red[24 + 2 * t2];
                float v1 = red[2 * t2 + 1] + red[8 + 2 * t2 + 1] + red[16 + 2 * t2 + 1] + red[24 + 2 * t2 + 1];
                asm volatile("st.relaxed.gpu.global.v2.u32 [%0], {%1,%2};" ::"l"(&g_mod[4 * bid + t2]), "r"(pack2(v0, v1)), "r"(*s_epoch) : "memory");
            }
        }
        PROF(0);
        const unsigned epoch = *s_epoch;
        {
            const int half = t2 & 1, rg = t2 >> 1;
            float a[8];
#pragma unroll
            for (int k = 0; k < 8; ++k) a[k] = 0.f;
            uint4 cv = *(const uint4*)(cvec + rg * 8);
#pragma unroll
            for (int b = 0; b < 2; ++b) {
                uint4 wv[4];
#pragma unroll
                for (int i = 0; i < 4; ++i) wv[i] = ldg_nc(wmod + (size_t)(rg * 8 + b * 4 + i) * 3072 + 1024 + 16 * bid + 8 * half);
                uint32_t c0 = b ? cv.z : cv.x, c1 = b ? cv.w : cv.y;
                float s[4] = {silu_bf(bf_lo(c0)), silu_bf(bf_hi(c0)), silu_bf(bf_lo(c1)), silu_bf(bf_hi(c1))};
#pragma unroll
                for (int i = 0; i < 4; ++i) {
                    a[0] = fmaf(s[i], bf_lo(wv[i].x), a[0]); a[1] = fmaf(s[i], bf_hi(wv[i].x), a[1]);
                    a[2] = fmaf(s[i], bf_lo(wv[i].y), a[2]); a[3] = fmaf(s[i], bf_hi(wv[i].y), a[3]);
                    a[4] = fmaf(s[i], bf_lo(wv[i].z), a[4]); a[5] = fmaf(s[i], bf_hi(wv[i].z), a[5]);
                    a[6] = fmaf(s[i], bf_lo(wv[i].w), a[6]); a[7] = fmaf(s[i], bf_hi(wv[i].w), a[7]);
                }
            }
            const bool u16 = lane & 16, u8 = lane & 8, u4 = lane & 4;
#pragma unroll
            for (int k = 0; k < 4; ++k) {
                float keep = u16 ? a[k + 4] : a[k], send = u16 ? a[k] : a[k + 4];
                a[k] = keep + __shfl_xor_sync(~0u, send, 16);
            }
#pragma unroll
            for (int k = 0; k < 2; ++k) {
                float keep = u8 ? a[k + 2] : a[k], send = u8 ? a[k] : a[k + 2];
                a[k] = keep + __shfl_xor_sync(~0u, send, 8);
            }
            {
                float keep = u4 ? a[1] : a[0], send = u4 ? a[0] : a[1];
                a[0] = keep + __shfl_xor_sync(~0u, send, 4);
            }
            a[0] += __shfl_xor_sync(~0u, a[0], 2);
            float* red2 = red + 64;
            if ((lane & 2) == 0) red2[(warp - 8) * 16 + half * 8 + (lane >> 2)] = a[0];
            bar_sync(2, 128);
            if (t2 < 8) {
                float v0 = red2[2 * t2] + red2[16 + 2 * t2] + red2[32 + 2 * t2] + red2[48 + 2 * t2];
                float v1 = red2[2 * t2 + 1] + red2[16 + 2 * t2 + 1] + red2[32 + 2 * t2 + 1] + red2[48 + 2 * t2 + 1];
                asm volatile("st.relaxed.gpu.global.v2.u32 [%0], {%1,%2};" ::"l"(&g_mod[512 + 8 * bid + t2]), "r"(pack2(v0, v1)), "r"(epoch) : "memory");
            }
        }
        PROF(1);
        if (warp == 8) {
            if (lane == 0) {
#pragma unroll 1
                for (int m = 0; m < 40; ++m) {
                    int pos = m % NSTAGE, rnd = m / NSTAGE;
                    int cnt = (pos == 0 ? 0 : 1) + rnd;
                    if (cnt > 0) mbar_wait(bars + 8 * (B_EMPTY + pos), (cnt - 1) & 1);
                    uint32_t fb = bars + 8 * (B_FULL + pos), dst = sb + pos * STAGE_BYTES;
                    mbar_expect(fb, STAGE_BYTES);
                    if (m < 4) {
                        tma2d(dst, &tmWo, 64 * r, 128 * m, fb);
                        tma2d(dst + 8192, &tmWo, 64 * r, 128 * m + 64, fb);
                    } else if (m < 28) {
                        int mm = m - 4, p = mm >> 3, rr = mm & 7;
                        tma2d(dst, &tmG, 176 * r + 64 * p, 64 * rr, fb);
                        tma2d(dst + 8192, &tmU, 176 * r + 64 * p, 64 * rr, fb);
                    } else {
                        int mm = m - 28, p = mm >> 2, i = (mm & 3) * 2;
                        tma2d(dst, &tmD, 64 * r, 176 * i + 64 * p, fb);
                        tma2d(dst + 8192, &tmD, 64 * r, 176 * (i + 1) + 64 * p, fb);
                    }
                }
            }
        } else if (warp == 9) {
            if (lane == 0 && j < 15) {
                uint4* dst = g_kv + (size_t)bid * 2048;
#pragma unroll 1
                for (int h = 0; h < 4; ++h) {
                    mbar_wait(bars + 8 * (B_KVW + h), 0);
                    bulk_s2g(dst + h * 512, sb + KV_OFF + h * 24576 + 16384, 8192);
                    asm volatile("cp.async.bulk.commit_group;" ::: "memory");
                }
                unsigned* fl = (unsigned*)&g_kvflag[bid * 2];
                asm volatile("cp.async.bulk.wait_group 3;" ::: "memory");
                asm volatile("st.release.gpu.global.u32 [%0], %1;" ::"l"(fl + 0), "r"(epoch) : "memory");
                asm volatile("cp.async.bulk.wait_group 2;" ::: "memory");
                asm volatile("st.release.gpu.global.u32 [%0], %1;" ::"l"(fl + 1), "r"(epoch) : "memory");
                asm volatile("cp.async.bulk.wait_group 1;" ::: "memory");
                asm volatile("st.release.gpu.global.u32 [%0], %1;" ::"l"(fl + 2), "r"(epoch) : "memory");
                asm volatile("cp.async.bulk.wait_group 0;" ::: "memory");
                asm volatile("st.release.gpu.global.u32 [%0], %1;" ::"l"(fl + 3), "r"(epoch) : "memory");
            }
            PROF(2);
        } else if (warp == 10) {
            if (lane == 0) {
                const int nn = j < 2 ? j : 2;
#pragma unroll 1
                for (int h = 0; h < 4; ++h) {
#pragma unroll 1
                    for (int n = 1; n <= nn; ++n) {
                        const unsigned* fl = (const unsigned*)&g_kvflag[(bid - 8 * n) * 2] + h;
                        unsigned v;
                        int it = 0;
                        do {
                            asm volatile("ld.acquire.gpu.global.u32 %0, [%1];" : "=r"(v) : "l"(fl) : "memory");
                            if (++it > SPIN_LIMIT) { DIE(); break; }
                        } while (v != epoch);
                    }
                    if (h == 0) mbar_wait(bars + 8 * B_KVW, 0);
                    fence_async_all();
                    uint32_t hb = bars + 8 * (B_HALO + h);
                    mbar_expect(hb, nn * 8192);
#pragma unroll 1
                    for (int n = 1; n <= nn; ++n)
                        bulk_g2s(sb + KV_OFF + h * 24576 + (2 - n) * 8192, g_kv + (size_t)(bid - 8 * n) * 2048 + h * 512, 8192, hb);
                }
            }
            PROF(2);
        } else {
            if (lane == 0) {
                prefetch_l2((const char*)wo + bid * 4096, 4096);
                prefetch_l2((const char*)wg + bid * 11008, 11008);
                prefetch_l2((const char*)wu + bid * 11008, 11008);
                prefetch_l2((const char*)wd + bid * 11008, 11008);
            }
            uint32_t* tab2 = (uint32_t*)(smem + TAB2_OFF);
#pragma unroll 1
            for (int q = 0; q < 9; ++q) {
                int e = q < 8 ? 768 + q * 64 + lane * 2 : (lane < 16 ? 512 + 32 * r + lane * 2 : 1280 + 32 * r + (lane - 16) * 2);
                uint4 v;
                int it = 0;
                do {
                    v = ld_rlx(&g_mod[e]);
                    if (++it > SPIN_LIMIT) { DIE(); break; }
                } while (v.y != epoch || v.w != epoch);
                if (q < 8) {
                    int ep = (q & 3) * 64 + lane * 2;
                    int isc = q >> 2;
                    uint32_t v0 = isc ? one_plus(v.x) : v.x, v1 = isc ? one_plus(v.z) : v.z;
                    int kap = ep >> 3, wi = ep & 7;
                    int o0 = (kap * 4 + (wi & 3)) * 4 + (wi >> 2) + (isc ? 0 : 2);
                    tab2[o0] = v0;
                    tab2[o0 + 4] = v1;
                } else {
                    float* g = (float*)(smem + GA_OFF) + lane * 4;
                    g[0] = bf_lo(v.x); g[1] = bf_hi(v.x); g[2] = bf_lo(v.z); g[3] = bf_hi(v.z);
                }
            }
            __syncwarp();
            if (lane == 0) mbar_arrive(bars + 8 * B_TAB2);
            PROF(2);
        }
    } else {
        asm volatile("setmaxnreg.inc.sync.aligned.u32 232;");
        const int w = warp, g = lane >> 2, t = lane & 3;
        const int row0 = 128 * j + 16 * w + g;
        uint4 A[32];
        float rs0, nm0, rs1, nm1;
        {
            const uint4* xp = (const uint4*)x + (size_t)row0 * 64 + t;
#pragma unroll
            for (int m = 0; m < 16; ++m) {
                uint4 u0 = ldg_nc(xp + 4 * m), u1 = ldg_nc(xp + 512 + 4 * m);
                A[2 * m] = make_uint4(u0.x, u1.x, u0.y, u1.y);
                A[2 * m + 1] = make_uint4(u0.z, u1.z, u0.w, u1.w);
            }
        }
        uint4 mv = ld_rlx(&g_mod[2 * threadIdx.x]);
        bar_sync(0, 384);
        {
            float s[2][4], q0[2][4], q1[2][4];
#pragma unroll
            for (int e = 0; e < 2; ++e)
#pragma unroll
                for (int i = 0; i < 4; ++i) s[e][i] = q0[e][i] = q1[e][i] = 0.f;
            const uint32_t ones = 0x3f803f80u;
#pragma unroll
            for (int k = 0; k < 32; ++k) {
                const int e = k & 1;
                const uint4 a = A[k];
                mma16816(s[e][0], s[e][1], s[e][2], s[e][3], a.x, a.y, a.z, a.w, ones, ones, s[e][0], s[e][1], s[e][2], s[e][3]);
                mma16816(q0[e][0], q0[e][1], q0[e][2], q0[e][3], a.x, a.y, a.z, a.w, a.x, a.z, q0[e][0], q0[e][1], q0[e][2], q0[e][3]);
                mma16816(q1[e][0], q1[e][1], q1[e][2], q1[e][3], a.x, a.y, a.z, a.w, a.y, a.w, q1[e][0], q1[e][1], q1[e][2], q1[e][3]);
            }
            float mean0 = (s[0][0] + s[1][0]) * (1.f / 512.f), mean1 = (s[0][2] + s[1][2]) * (1.f / 512.f);
            float d0 = (g & 1) ? q0[0][1] + q0[1][1] : q0[0][0] + q0[1][0];
            float d1 = (g & 1) ? q1[0][3] + q1[1][3] : q1[0][2] + q1[1][2];
            d0 = __shfl_sync(~0u, d0, g * 4 + (g >> 1));
            d1 = __shfl_sync(~0u, d1, g * 4 + (g >> 1));
            float v0 = fmaxf(d0 * (1.f / 512.f) - mean0 * mean0, 0.f), v1 = fmaxf(d1 * (1.f / 512.f) - mean1 * mean1, 0.f);
            rs0 = rsqrtf(v0 + 1e-5f); rs1 = rsqrtf(v1 + 1e-5f);
            nm0 = -mean0 * rs0; nm1 = -mean1 * rs1;
        }
        PROF(0);
        mbar_wait(bars + 8 * B_EPOCH, 0);
        const unsigned epoch = *(volatile unsigned*)(smem + MISC_OFF);
        const uint32_t par = epoch & 1u;
        {
            int it = 0;
#pragma unroll 1
            while (mv.y != epoch || mv.w != epoch) {
                mv = ld_rlx(&g_mod[2 * threadIdx.x]);
                if (++it > SPIN_LIMIT) { DIE(); break; }
            }
            const int i = threadIdx.x & 127, isc = threadIdx.x >> 7;
            const int m = i >> 3, tt = (i >> 1) & 3, p = i & 1;
            uint32_t v0 = isc ? one_plus(mv.x) : mv.x, v1 = isc ? one_plus(mv.z) : mv.z;
            *(uint2*)(smem + TAB1_OFF + ((2 * m + p) * 4 + tt) * 16 + (isc ? 0 : 8)) = make_uint2(v0, v1);
        }
        bar_sync(1, 256);
        if (bid == 0 && threadIdx.x == 0)
            asm volatile("st.relaxed.gpu.global.u32 [%0], %1;" ::"l"(&g_epoch), "r"(epoch) : "memory");
        PROF(1);

        uint32_t qf[16];
        {
            uint32_t kv[32];
            {
                float acc[64];
#pragma unroll
                for (int kb = 0; kb < 8; ++kb) {
                    const int pos = kb < 6 ? 7 + kb : kb - 5;
#pragma unroll
                    for (int s = 0; s < 4; ++s)
                        ln_mod(A[4 * kb + s], lds128(sb + TAB1_OFF + ((4 * kb + s) * 4 + t) * 16), rs0, nm0, rs1, nm1);
                    mbar_wait(bars + 8 * (B_FULL + pos), 0);
                    const uint64_t d = bdesc(sb + pos * STAGE_BYTES);
                    WG_FENCE();
#pragma unroll
                    for (int s = 0; s < 4; ++s) {
                        if (kb == 0 && s == 0) wgmma128<0>(acc, A[4 * kb + s], d);
                        else wgmma128<1>(acc, A[4 * kb + s], d + s * 128);
                    }
                    WG_COMMIT();
                }
                WG_WAIT(0);
                PROF(2);
#pragma unroll
                for (int i = 0; i < 32; ++i) kv[i] = pack2(acc[2 * i], acc[2 * i + 1]);
            }
            if (lane == 0) { mbar_arrive(bars + 8 * (B_EMPTY + 1)); mbar_arrive(bars + 8 * (B_EMPTY + 2)); }
            float accq[32];
            const uint32_t kvw = sb + KV_OFF + (16 + w) * 1024 + lane * 16;
#pragma unroll
            for (int h = 0; h < 4; ++h) {
                mbar_wait(bars + 8 * (B_FULL + 3 + h), 0);
                const uint64_t d = bdesc(sb + (3 + h) * STAGE_BYTES);
                WG_FENCE();
#pragma unroll
                for (int s = 0; s < 8; ++s) {
                    if (h == 0 && s == 0) wgmma64<0>(accq, A[8 * h + s], d);
                    else wgmma64<1>(accq, A[8 * h + s], d + s * 128);
                }
                WG_COMMIT();
                if (h == 0) bar_sync(1, 256);
                sts128(kvw + h * 24576, kv[4 * h], kv[4 * h + 2], kv[4 * h + 1], kv[4 * h + 3]);
                sts128(kvw + h * 24576 + 512, movmat(kv[16 + 4 * h]), movmat(kv[16 + 4 * h + 1]), movmat(kv[16 + 4 * h + 2]),
                       movmat(kv[16 + 4 * h + 3]));
                if (j < 2) {
                    sts128(kvw + h * 24576 - 16384, 0, 0, 0, 0);
                    sts128(kvw + h * 24576 - 16384 + 512, 0, 0, 0, 0);
                    if (j == 0) {
                        sts128(kvw + h * 24576 - 8192, 0, 0, 0, 0);
                        sts128(kvw + h * 24576 - 8192 + 512, 0, 0, 0, 0);
                    }
                }
                fence_async_smem();
                __syncwarp();
                if (lane == 0) mbar_arrive(bars + 8 * (B_KVW + h));
            }
            WG_WAIT(0);
            if (lane == 0) {
#pragma unroll
                for (int q = 0; q < 4; ++q) mbar_arrive(bars + 8 * (B_EMPTY + 3 + q));
            }
#pragma unroll
            for (int i = 0; i < 16; ++i) qf[i] = pack2(accq[2 * i], accq[2 * i + 1]);
        }
        PROF(3);
        uint4* const o_base = g_o + (size_t)(j * 8 + w) * 1024 + lane;
        uint4* const x1_base = g_x1 + (size_t)(j * 8 + w) * 1024 + lane;
        uint4* const st_base = g_st + (size_t)(j * 8 + w) * 64;
        st_rlx(o_base + (4 * r + 3) * 32, par ^ 1u, 0, 0, 0);
        if (lane < 8) st_rlx(st_base + r * 8 + lane, par ^ 1u, 0, 0, 0);

        {
            const float CS = 0.25f * 1.4426950408889634f;
            const int nv = 16 - 8 * j - w;
            const uint32_t mD = ((2 * t <= g) ? 0xffffu : 0u) | ((2 * t + 1 <= g) ? 0xffff0000u : 0u);
#pragma unroll 1
            for (int h = 0; h < 4; ++h) {
                mbar_wait(bars + 8 * (B_KVW + h), 0);
                mbar_wait(bars + 8 * (B_HALO + h), 0);
                const uint32_t kb = sb + KV_OFF + h * 24576 + w * 1024 + lane * 16;
                float S[16][8];
#pragma unroll
                for (int i = 1; i < 16; ++i) {
                    uint4 k = lds128(kb + i * 1024);
                    float bias = i >= nv ? 0.f : -1e30f;
                    mma16816(S[i][0], S[i][1], S[i][2], S[i][3], qf[0], qf[1], qf[2], qf[3], k.x, k.y, bias, bias, bias, bias);
                    mma16816(S[i][4], S[i][5], S[i][6], S[i][7], qf[0], qf[1], qf[2], qf[3], k.z, k.w, bias, bias, bias, bias);
                }
                {
                    float d[8], o[8];
                    uint4 k = lds128(kb + 16 * 1024);
                    mma16816(d[0], d[1], d[2], d[3], qf[0], qf[1], qf[2], qf[3], k.x, k.y, 0.f, 0.f, 0.f, 0.f);
                    mma16816(d[4], d[5], d[6], d[7], qf[0], qf[1], qf[2], qf[3], k.z, k.w, 0.f, 0.f, 0.f, 0.f);
                    k = lds128(kb);
                    float bias = 0 >= nv ? 0.f : -1e30f;
                    mma16816(o[0], o[1], o[2], o[3], qf[0], qf[1], qf[2], qf[3], k.x, k.y, bias, bias, bias, bias);
                    mma16816(o[4], o[5], o[6], o[7], qf[0], qf[1], qf[2], qf[3], k.z, k.w, bias, bias, bias, bias);
                    S[0][0] = (2 * t <= g) ? d[0] : o[0];
                    S[0][1] = (2 * t + 1 <= g) ? d[1] : o[1];
                    S[0][2] = d[2]; S[0][3] = d[3]; S[0][4] = o[4]; S[0][5] = o[5];
                    S[0][6] = (2 * t <= g) ? d[6] : o[6];
                    S[0][7] = (2 * t + 1 <= g) ? d[7] : o[7];
                }
                float m0a = fmaxf(S[0][0], S[0][1]), m0b = fmaxf(S[0][4], S[0][5]);
                float m1a = fmaxf(S[0][2], S[0][3]), m1b = fmaxf(S[0][6], S[0][7]);
#pragma unroll
                for (int i = 1; i < 16; ++i) {
                    m0a = fmaxf(m0a, fmaxf(S[i][0], S[i][1])); m0b = fmaxf(m0b, fmaxf(S[i][4], S[i][5]));
                    m1a = fmaxf(m1a, fmaxf(S[i][2], S[i][3])); m1b = fmaxf(m1b, fmaxf(S[i][6], S[i][7]));
                }
                float m0 = fmaxf(m0a, m0b), m1 = fmaxf(m1a, m1b);
                m0 = fmaxf(m0, __shfl_xor_sync(~0u, m0, 1)); m1 = fmaxf(m1, __shfl_xor_sync(~0u, m1, 1));
                m0 = fmaxf(m0, __shfl_xor_sync(~0u, m0, 2)); m1 = fmaxf(m1, __shfl_xor_sync(~0u, m1, 2));
                const float c0 = -m0 * CS, c1 = -m1 * CS;
                float O[8], l0 = 0.f, l1 = 0.f;
#pragma unroll
                for (int i = 0; i < 8; ++i) O[i] = 0.f;
#pragma unroll
                for (int i = 0; i < 16; ++i) {
                    float p0 = ex2f(fmaf(S[i][0], CS, c0)), p1 = ex2f(fmaf(S[i][1], CS, c0));
                    float p2 = ex2f(fmaf(S[i][2], CS, c1)), p3 = ex2f(fmaf(S[i][3], CS, c1));
                    float p4 = ex2f(fmaf(S[i][4], CS, c0)), p5 = ex2f(fmaf(S[i][5], CS, c0));
                    float p6 = ex2f(fmaf(S[i][6], CS, c1)), p7 = ex2f(fmaf(S[i][7], CS, c1));
                    l0 += (p0 + p1) + (p4 + p5);
                    l1 += (p2 + p3) + (p6 + p7);
                    uint32_t a0 = pack2(p0, p1), a1 = pack2(p2, p3), a2 = pack2(p4, p5), a3 = pack2(p6, p7);
                    uint4 v = lds128(kb + i * 1024 + 512);
                    if (i == 0) {
                        mma16816(O[0], O[1], O[2], O[3], a0 & ~mD, 0u, a2, a3 & ~mD, v.x, v.y, O[0], O[1], O[2], O[3]);
                        mma16816(O[4], O[5], O[6], O[7], a0 & ~mD, 0u, a2, a3 & ~mD, v.z, v.w, O[4], O[5], O[6], O[7]);
                        v = lds128(kb + 16 * 1024 + 512);
                        mma16816(O[0], O[1], O[2], O[3], a0 & mD, a1, 0u, a3 & mD, v.x, v.y, O[0], O[1], O[2], O[3]);
                        mma16816(O[4], O[5], O[6], O[7], a0 & mD, a1, 0u, a3 & mD, v.z, v.w, O[4], O[5], O[6], O[7]);
                    } else {
                        mma16816(O[0], O[1], O[2], O[3], a0, a1, a2, a3, v.x, v.y, O[0], O[1], O[2], O[3]);
                        mma16816(O[4], O[5], O[6], O[7], a0, a1, a2, a3, v.z, v.w, O[4], O[5], O[6], O[7]);
                    }
                }
                l0 += __shfl_xor_sync(~0u, l0, 1); l1 += __shfl_xor_sync(~0u, l1, 1);
                l0 += __shfl_xor_sync(~0u, l0, 2); l1 += __shfl_xor_sync(~0u, l1, 2);
                const float i0 = __fdividef(1.f, l0), i1 = __fdividef(1.f, l1);
#pragma unroll
                for (int i = 0; i < 12; ++i) qf[i] = qf[i + 4];
                st_rlx(o_base + (4 * r + h) * 32, tagw(pack2(O[0] * i0, O[1] * i0), par), pack2(O[2] * i1, O[3] * i1),
                       pack2(O[4] * i0, O[5] * i0), pack2(O[6] * i1, O[7] * i1));
            }
            __syncwarp();
            if (lane == 0) {
#pragma unroll
                for (int q = 7; q < 13; ++q) mbar_arrive(bars + 8 * (B_EMPTY + q));
            }
        }
        PROF(4);

        uint32_t x1bits;
        {
#pragma unroll
            for (int h = 0; h < 4; ++h)
#pragma unroll
                for (int i = 0; i < 8; ++i) A[8 * h + i] = ld_rlx(o_base + (4 * i + h) * 32);
            uint32_t xr[16];
            {
                const uint32_t* xp = (const uint32_t*)(x + (size_t)row0 * 512 + 64 * r) + t;
#pragma unroll
                for (int b = 0; b < 8; ++b) { xr[2 * b] = __ldg(xp + 4 * b); xr[2 * b + 1] = __ldg(xp + 2048 + 4 * b); }
            }
            float acc[32];
#pragma unroll
            for (int m = 0; m < 4; ++m) mbar_wait(bars + 8 * (B_FULL + wpos(m)), wpar(m));
            const uint64_t d0 = bdesc(sb);
#pragma unroll
            for (int h = 0; h < 4; ++h) {
                validate<8>(&A[8 * h], o_base + h * 32, [](int i) { return 128 * i; }, par);
                WG_FENCE();
#pragma unroll
                for (int i = 0; i < 8; ++i) {
                    if (h == 0 && i == 0) wgmma64<0>(acc, A[8 * h + i], d0);
                    else wgmma64<1>(acc, A[8 * h + i], d0 + i * 512 + h * 128);
                }
                WG_COMMIT();
            }
            mbar_wait(bars + 8 * B_TAB2, 0);
            WG_WAIT(0);
            PROF(5);
            if (lane == 0) {
#pragma unroll
                for (int m = 0; m < 4; ++m) mbar_arrive(bars + 8 * (B_EMPTY + wpos(m)));
            }
            float s0 = 0.f, s1 = 0.f, q0 = 0.f, q1 = 0.f;
            uint32_t xo[16];
#pragma unroll
            for (int b = 0; b < 8; ++b) {
                const float2 ga = *(const float2*)(smem + GA_OFF + (8 * b + 2 * t) * 4);
                uint32_t p0 = pack2(fmaf(ga.x, acc[4 * b], bf_lo(xr[2 * b])), fmaf(ga.y, acc[4 * b + 1], bf_hi(xr[2 * b])));
                uint32_t p1 = pack2(fmaf(ga.x, acc[4 * b + 2], bf_lo(xr[2 * b + 1])), fmaf(ga.y, acc[4 * b + 3], bf_hi(xr[2 * b + 1])));
                xo[2 * b] = p0; xo[2 * b + 1] = p1;
                float a = bf_lo(p0), c = bf_hi(p0), e = bf_lo(p1), f = bf_hi(p1);
                s0 += a + c; q0 = fmaf(a, a, fmaf(c, c, q0));
                s1 += e + f; q1 = fmaf(e, e, fmaf(f, f, q1));
            }
            s0 += __shfl_xor_sync(~0u, s0, 1); q0 += __shfl_xor_sync(~0u, q0, 1);
            s1 += __shfl_xor_sync(~0u, s1, 1); q1 += __shfl_xor_sync(~0u, q1, 1);
            s0 += __shfl_xor_sync(~0u, s0, 2); q0 += __shfl_xor_sync(~0u, q0, 2);
            s1 += __shfl_xor_sync(~0u, s1, 2); q1 += __shfl_xor_sync(~0u, q1, 2);
            if (t == 0) st_rlx(st_base + r * 8 + g, tagw(__float_as_uint(q0), par), __float_as_uint(s0), __float_as_uint(q1), __float_as_uint(s1));
#pragma unroll
            for (int i = 0; i < 4; ++i) st_rlx(x1_base + (4 * r + i) * 32, tagw(xo[4 * i], par), xo[4 * i + 1], xo[4 * i + 2], xo[4 * i + 3]);
            x1bits = (xo[0] & 1u) | ((xo[4] & 1u) << 1) | ((xo[8] & 1u) << 2) | ((xo[12] & 1u) << 3);
        }
        PROF(6);
        {
            uint4 sv[2];
            const uint4* sp = st_base + 16 * t + g;
            sv[0] = ld_rlx(sp); sv[1] = ld_rlx(sp + 8);
            validate<2>(sv, sp, [](int i) { return 8 * i; }, par);
#pragma unroll
            for (int i = 0; i < 32; ++i) A[i] = ld_rlx(x1_base + i * 32);
            float q0 = __uint_as_float(sv[0].x) + __uint_as_float(sv[1].x), s0 = __uint_as_float(sv[0].y) + __uint_as_float(sv[1].y);
            float q1 = __uint_as_float(sv[0].z) + __uint_as_float(sv[1].z), s1 = __uint_as_float(sv[0].w) + __uint_as_float(sv[1].w);
            s0 += __shfl_xor_sync(~0u, s0, 1); q0 += __shfl_xor_sync(~0u, q0, 1);
            s1 += __shfl_xor_sync(~0u, s1, 1); q1 += __shfl_xor_sync(~0u, q1, 1);
            s0 += __shfl_xor_sync(~0u, s0, 2); q0 += __shfl_xor_sync(~0u, q0, 2);
            s1 += __shfl_xor_sync(~0u, s1, 2); q1 += __shfl_xor_sync(~0u, q1, 2);
            float mean0 = s0 * (1.f / 512.f), mean1 = s1 * (1.f / 512.f);
            float v0 = fmaxf(q0 * (1.f / 512.f) - mean0 * mean0, 0.f), v1 = fmaxf(q1 * (1.f / 512.f) - mean1 * mean1, 0.f);
            rs0 = rsqrtf(v0 + 1e-5f); rs1 = rsqrtf(v1 + 1e-5f);
            nm0 = -mean0 * rs0; nm1 = -mean1 * rs1;
        }
        PROF(7);
        uint4* const hh_base = g_hh + (size_t)(j * 8 + w) * (8 * 11 * 32) + lane;
        {
            float acc[64];
#pragma unroll
            for (int p = 0; p < 2; ++p) {
#pragma unroll
                for (int i = 0; i < 8; ++i) {
                    const int m = 4 + 8 * p + i;
                    if (p == 0) {
                        validate<4>(&A[4 * i], x1_base + 128 * i, [](int c) { return 32 * c; }, par);
#pragma unroll
                        for (int c = 0; c < 4; ++c)
                            ln_mod(A[4 * i + c], lds128(sb + TAB2_OFF + ((4 * i + c) * 4 + t) * 16), rs0, nm0, rs1, nm1);
                    }
                    mbar_wait(bars + 8 * (B_FULL + wpos(m)), wpar(m));
                    const uint64_t d = bdesc(sb + wpos(m) * STAGE_BYTES);
                    WG_FENCE();
#pragma unroll
                    for (int c = 0; c < 4; ++c) {
                        if (i == 0 && c == 0) wgmma128<0>(acc, A[4 * i + c], d);
                        else wgmma128<1>(acc, A[4 * i + c], d + c * 128);
                    }
                    WG_COMMIT();
                    if (i > 0) {
                        WG_WAIT(1);
                        if (lane == 0) mbar_arrive(bars + 8 * (B_EMPTY + wpos(m - 1)));
                    }
                }
                WG_WAIT(0);
                if (lane == 0) mbar_arrive(bars + 8 * (B_EMPTY + wpos(4 + 8 * p + 7)));
#pragma unroll
                for (int c = 0; c < 4; ++c) {
                    uint32_t hv[4];
#pragma unroll
                    for (int e = 0; e < 4; ++e)
                        hv[e] = hmul2(pack2(acc[8 * c + 2 * e], acc[8 * c + 2 * e + 1]), pack2(acc[32 + 8 * c + 2 * e], acc[32 + 8 * c + 2 * e + 1]));
                    st_rlx(hh_base + (r * 11 + 4 * p + c) * 32, tagw(hv[0], par), hv[1], hv[2], hv[3]);
                }
                PROF(8 + p);
            }
        }
        {
            float ag[24], au[24];
#pragma unroll
            for (int i = 0; i < 8; ++i) {
                const int m = 20 + i;
                mbar_wait(bars + 8 * (B_FULL + wpos(m)), wpar(m));
                const uint64_t d = bdesc(sb + wpos(m) * STAGE_BYTES);
                WG_FENCE();
#pragma unroll
                for (int c = 0; c < 4; ++c) {
                    if (i == 0 && c == 0) {
                        wgmma48<0>(ag, A[4 * i + c], d);
                        wgmma48<0>(au, A[4 * i + c], d + 512);
                    } else {
                        wgmma48<1>(ag, A[4 * i + c], d + c * 128);
                        wgmma48<1>(au, A[4 * i + c], d + 512 + c * 128);
                    }
                }
                WG_COMMIT();
                if (i > 0) {
                    WG_WAIT(1);
                    if (lane == 0) mbar_arrive(bars + 8 * (B_EMPTY + wpos(m - 1)));
                }
            }
            WG_WAIT(0);
#pragma unroll
            for (int c = 0; c < 3; ++c) {
                uint32_t hv[4];
#pragma unroll
                for (int e = 0; e < 4; ++e)
                    hv[e] = hmul2(pack2(ag[8 * c + 2 * e], ag[8 * c + 2 * e + 1]), pack2(au[8 * c + 2 * e], au[8 * c + 2 * e + 1]));
                st_rlx(hh_base + (r * 11 + 8 + c) * 32, tagw(hv[0], par), hv[1], hv[2], hv[3]);
            }
        }
        PROF(10);
        {
            float acc[32];
            auto off8 = [](int k) { return ((k >> 2) * 11 + (k & 3)) * 32; };
            auto off6 = [](int k) { return ((k / 3) * 11 + (k % 3)) * 32; };
#define HGRP(gi) (hh_base + (((gi) & 3) * 22 + 4 * ((gi) >> 2)) * 32)
#pragma unroll
            for (int gi = 0; gi < 4; ++gi)
#pragma unroll
                for (int k = 0; k < 8; ++k) A[8 * gi + k] = ld_rlx(HGRP(gi) + off8(k));
            uint4 X1[4];
#pragma unroll
            for (int i = 0; i < 4; ++i) X1[i] = ld_rlx(x1_base + (4 * r + i) * 32);
#pragma unroll
            for (int gi = 0; gi < 12; ++gi) {
                const int m = 28 + gi;
                uint4* R = &A[8 * (gi & 3)];
                if (gi < 8) validate<8>(R, HGRP(gi), off8, par);
                else validate<6>(R, HGRP(gi), off6, par);
                mbar_wait(bars + 8 * (B_FULL + wpos(m)), wpar(m));
                const uint64_t d = bdesc(sb + wpos(m) * STAGE_BYTES);
                WG_FENCE();
                if (gi < 8) {
#pragma unroll
                    for (int k = 0; k < 8; ++k) {
                        if (gi == 0 && k == 0) wgmma64<0>(acc, R[k], d);
                        else wgmma64<1>(acc, R[k], d + k * 128);
                    }
                } else {
#pragma unroll
                    for (int k = 0; k < 6; ++k) wgmma64<1>(acc, R[k], d + ((k / 3) * 4 + k % 3) * 128);
                }
                WG_COMMIT();
                if (gi > 0 && gi + 3 < 12) {
                    WG_WAIT(1);
                    uint4* N = &A[8 * ((gi + 3) & 3)];
                    if (gi + 3 < 8) {
#pragma unroll
                        for (int k = 0; k < 8; ++k) N[k] = ld_rlx(HGRP(gi + 3) + off8(k));
                    } else {
#pragma unroll
                        for (int k = 0; k < 6; ++k) N[k] = ld_rlx(HGRP(gi + 3) + off6(k));
                    }
                }
            }
            WG_WAIT(0);
            PROF(11);
#pragma unroll
            for (int i = 0; i < 4; ++i) {
                uint32_t xw[4] = {(X1[i].x & ~1u) | ((x1bits >> i) & 1u), X1[i].y, X1[i].z, X1[i].w};
                uint32_t o[4];
#pragma unroll
                for (int e = 0; e < 4; ++e) {
                    const float2 gb = *(const float2*)(smem + GB_OFF + (16 * i + 8 * (e >> 1) + 2 * t) * 4);
                    o[e] = pack2(fmaf(gb.x, acc[8 * i + 2 * e], bf_lo(xw[e])), fmaf(gb.y, acc[8 * i + 2 * e + 1], bf_hi(xw[e])));
                }
                const bool t1 = t & 1, t2b = t & 2;
                uint32_t k0 = t1 ? o[1] : o[0], s0 = t1 ? o[0] : o[1];
                uint32_t k1 = t1 ? o[3] : o[2], s1 = t1 ? o[2] : o[3];
                s0 = __shfl_xor_sync(~0u, s0, 1); s1 = __shfl_xor_sync(~0u, s1, 1);
                uint32_t a0 = t1 ? s0 : k0, a1 = t1 ? k0 : s0;
                uint32_t b0 = t1 ? s1 : k1, b1 = t1 ? k1 : s1;
                uint32_t kk0 = t2b ? b0 : a0, kk1 = t2b ? b1 : a1, ss0 = t2b ? a0 : b0, ss1 = t2b ? a1 : b1;
                ss0 = __shfl_xor_sync(~0u, ss0, 2); ss1 = __shfl_xor_sync(~0u, ss1, 2);
                uint4 res = t2b ? make_uint4(ss0, ss1, kk0, kk1) : make_uint4(kk0, kk1, ss0, ss1);
                *(uint4*)(out + (size_t)(row0 + 8 * (t & 1)) * 512 + 64 * r + 16 * i + 8 * (t >> 1)) = res;
            }
        }
        PROF(12);
    }
}

typedef CUresult (*EncodeFn)(CUtensorMap*, CUtensorMapDataType, cuuint32_t, void*, const cuuint64_t*, const cuuint64_t*,
                             const cuuint32_t*, const cuuint32_t*, CUtensorMapInterleave, CUtensorMapSwizzle,
                             CUtensorMapL2promotion, CUtensorMapFloatOOBfill);

void make2d(EncodeFn enc, CUtensorMap* m, const void* p, uint64_t cols, uint64_t rows) {
    cuuint64_t dims[2] = {cols, rows};
    cuuint64_t str[1] = {cols * 2};
    cuuint32_t box[2] = {64, 64}, es[2] = {1, 1};
    enc(m, CU_TENSOR_MAP_DATA_TYPE_BFLOAT16, 2, (void*)p, dims, str, box, es, CU_TENSOR_MAP_INTERLEAVE_NONE,
        CU_TENSOR_MAP_SWIZZLE_128B, CU_TENSOR_MAP_L2_PROMOTION_L2_128B, CU_TENSOR_MAP_FLOAT_OOB_FILL_NONE);
}

}

extern "C" void kernel_launch(void* const* d_in, const int* in_sizes, int n_in, void* d_out, int out_size) {
    const __nv_bfloat16* x = (const __nv_bfloat16*)d_in[0];
    const __nv_bfloat16* wqkv = (const __nv_bfloat16*)d_in[1];
    const __nv_bfloat16* wo = (const __nv_bfloat16*)d_in[2];
    const __nv_bfloat16* wg = (const __nv_bfloat16*)d_in[4];
    const __nv_bfloat16* wu = (const __nv_bfloat16*)d_in[5];
    const __nv_bfloat16* wd = (const __nv_bfloat16*)d_in[6];
    const __nv_bfloat16* c = (const __nv_bfloat16*)d_in[7];
    const __nv_bfloat16* wmod = (const __nv_bfloat16*)d_in[8];

    void* fn = nullptr;
    cudaDriverEntryPointQueryResult qr;
    cudaGetDriverEntryPoint("cuTensorMapEncodeTiled", &fn, cudaEnableDefault, &qr);
    EncodeFn enc = (EncodeFn)fn;
    CUtensorMap tmQKV, tmWo, tmG, tmU, tmD;
    {
        cuuint64_t dims[5] = {1536, 2, 4, 4, 16};
        cuuint64_t str[4] = {3072, 8 * 3072, 2 * 3072, 32 * 3072};
        cuuint32_t box[5] = {64, 2, 4, 4, 2}, es[5] = {1, 1, 1, 1, 1};
        enc(&tmQKV, CU_TENSOR_MAP_DATA_TYPE_BFLOAT16, 5, (void*)wqkv, dims, str, box, es, CU_TENSOR_MAP_INTERLEAVE_NONE,
            CU_TENSOR_MAP_SWIZZLE_128B, CU_TENSOR_MAP_L2_PROMOTION_L2_128B, CU_TENSOR_MAP_FLOAT_OOB_FILL_NONE);
    }
    make2d(enc, &tmWo, wo, 512, 512);
    make2d(enc, &tmG, wg, 1376, 512);
    make2d(enc, &tmU, wu, 1376, 512);
    make2d(enc, &tmD, wd, 512, 1376);
    cudaFuncSetAttribute(fused_kernel, cudaFuncAttributeMaxDynamicSharedMemorySize, SMEM_BYTES);
    fused_kernel<<<128, 384, SMEM_BYTES, cudaStreamPerThread>>>(tmQKV, tmWo, tmG, tmU, tmD, x, wo, wg, wu, wd, c, wmod,
                                                               (__nv_bfloat16*)d_out);
}
```

```cpp
#include <cuda_runtime.h>
#include <cuda_bf16.h>
#include <cuda.h>
#include <stdint.h>

namespace {

constexpr int NSTAGE = 11;
constexpr int STAGE_BYTES = 16384;
constexpr int KV_OFF = 5 * STAGE_BYTES;
constexpr int TAB1_OFF = NSTAGE * STAGE_BYTES;
constexpr int TAB2_OFF = TAB1_OFF + 2048;
constexpr int GA_OFF = TAB2_OFF + 2048;
constexpr int GB_OFF = GA_OFF + 256;
constexpr int RED_OFF = GB_OFF + 256;
constexpr int MISC_OFF = RED_OFF + 576;
constexpr int BAR_OFF = MISC_OFF + 64;
constexpr int B_FULL = 0, B_EMPTY = 11, B_KVW = 22, B_HALO = 26, B_TAB2 = 30, B_PUB = 31, NBAR = 32;
constexpr int SMEM_BYTES = BAR_OFF + NBAR * 8;

#define NX0 8
constexpr int SPIN_LIMIT = 1 << 22;
#define DIE() asm volatile("st.global.u32 [%0], %1;" ::"l"(0ull), "r"(0) : "memory")

__device__ uint4 g_kv[16 * 8 * 2048];
__device__ uint4 g_o[16 * 8 * 32 * 32];
__device__ uint4 g_x1[16 * 8 * 32 * 32];
__device__ uint4 g_st[16 * 8 * 8 * 8];
__device__ uint4 g_hh[16 * 8 * 8 * 11 * 32];
__device__ uint4 g_part[16 * 8 * 8 * 12 * 32];
__device__ uint4 g_m1[512];
__device__ uint4 g_m2[512];
__device__ uint4 g_rs[2048];
__device__ uint4 g_kvflag[16 * 8 * 2];
__device__ unsigned g_epoch;
#define PROF(i) do {} while (0)

__device__ __forceinline__ uint32_t s2u(const void* p) { return (uint32_t)__cvta_generic_to_shared(p); }
__device__ __forceinline__ void mbar_init(uint32_t b, int c) {
    asm volatile("mbarrier.init.shared::cta.b64 [%0], %1;" ::"r"(b), "r"(c) : "memory");
}
__device__ __forceinline__ void mbar_expect(uint32_t b, uint32_t bytes) {
    asm volatile("mbarrier.arrive.expect_tx.shared::cta.b64 _, [%0], %1;" ::"r"(b), "r"(bytes) : "memory");
}
__device__ __forceinline__ void mbar_arrive(uint32_t b) {
    asm volatile("mbarrier.arrive.shared::cta.b64 _, [%0];" ::"r"(b) : "memory");
}
__device__ __forceinline__ void mbar_wait(uint32_t b, uint32_t ph) {
    asm volatile(
        "{\n.reg .pred p;\n.reg .u32 n;\n"
        "mov.u32 n, 0;\n"
        "LOOP_%=:\n"
        "mbarrier.try_wait.parity.shared::cta.b64 p, [%0], %1;\n"
        "@p bra DONE_%=;\n"
        "add.u32 n, n, 1;\n"
        "setp.lt.u32 p, n, %2;\n"
        "@p bra LOOP_%=;\n"
        "st.global.u32 [%3], n;\n"
        "DONE_%=:\n}" ::"r"(b), "r"(ph), "n"(SPIN_LIMIT), "l"(0ull) : "memory");
}
__device__ __forceinline__ void bar_sync(int id, int n) { asm volatile("bar.sync %0, %1;" ::"r"(id), "r"(n) : "memory"); }
__device__ __forceinline__ void bar_arrive(int id, int n) { asm volatile("bar.arrive %0, %1;" ::"r"(id), "r"(n) : "memory"); }
__device__ __forceinline__ void fence_async_smem() { asm volatile("fence.proxy.async.shared::cta;" ::: "memory"); }
__device__ __forceinline__ void fence_async_all() { asm volatile("fence.proxy.async;" ::: "memory"); }

__device__ __forceinline__ void tma2d(uint32_t dst, const CUtensorMap* m, int c0, int c1, uint32_t bar) {
    asm volatile("cp.async.bulk.tensor.2d.shared::cluster.global.mbarrier::complete_tx::bytes [%0], [%1, {%3, %4}], [%2];"
                 ::"r"(dst), "l"(m), "r"(bar), "r"(c0), "r"(c1) : "memory");
}
__device__ __forceinline__ void tma5d(uint32_t dst, const CUtensorMap* m, int c0, int c4, uint32_t bar) {
    asm volatile("cp.async.bulk.tensor.5d.shared::cluster.global.mbarrier::complete_tx::bytes [%0], [%1, {%3, %5, %5, %5, %4}], [%2];"
                 ::"r"(dst), "l"(m), "r"(bar), "r"(c0), "r"(c4), "r"(0) : "memory");
}
__device__ __forceinline__ void bulk_g2s(uint32_t dst, const void* src, uint32_t bytes, uint32_t bar) {
    asm volatile("cp.async.bulk.shared::cluster.global.mbarrier::complete_tx::bytes [%0], [%1], %2, [%3];"
                 ::"r"(dst), "l"(src), "r"(bytes), "r"(bar) : "memory");
}
__device__ __forceinline__ void bulk_s2g(void* dst, uint32_t src, uint32_t bytes) {
    asm volatile("cp.async.bulk.global.shared::cta.bulk_group [%0], [%1], %2;" ::"l"(dst), "r"(src), "r"(bytes) : "memory");
}
__device__ __forceinline__ void prefetch_l2(const void* p, uint32_t bytes) {
    asm volatile("cp.async.bulk.prefetch.L2.global [%0], %1;" ::"l"(p), "r"(bytes) : "memory");
}
__device__ __forceinline__ uint4 ldg_nc(const void* p) {
    uint4 v;
    asm volatile("ld.global.nc.v4.u32 {%0,%1,%2,%3}, [%4];" : "=r"(v.x), "=r"(v.y), "=r"(v.z), "=r"(v.w) : "l"(p));
    return v;
}
__device__ __forceinline__ uint4 ld_rlx(const void* p) {
    uint4 v;
    asm volatile("{\n.reg .b128 t;\n.reg .b64 a, b;\nld.relaxed.gpu.global.b128 t, [%4];\nmov.b128 {a, b}, t;\n"
                 "mov.b64 {%0,%1}, a;\nmov.b64 {%2,%3}, b;\n}"
                 : "=r"(v.x), "=r"(v.y), "=r"(v.z), "=r"(v.w) : "l"(p) : "memory");
    return v;
}
__device__ __forceinline__ void st_rlx(void* p, uint32_t x, uint32_t y, uint32_t z, uint32_t w) {
    asm volatile("{\n.reg .b128 t;\n.reg .b64 a, b;\nmov.b64 a, {%1,%2};\nmov.b64 b, {%3,%4};\nmov.b128 t, {a, b};\n"
                 "st.relaxed.gpu.global.b128 [%0], t;\n}" ::"l"(p), "r"(x), "r"(y), "r"(z), "r"(w) : "memory");
}
__device__ __forceinline__ uint32_t tagw(uint32_t x, uint32_t par) { return (x & ~1u) | par; }
template <int N, class F>
__device__ __forceinline__ void validate(uint4* v, const uint4* p, F off, uint32_t par) {
    uint32_t all1 = v[0].x, any1 = v[0].x;
#pragma unroll
    for (int i = 1; i < N; ++i) { all1 &= v[i].x; any1 |= v[i].x; }
    uint32_t bad = (par ? ~all1 : any1) & 1u;
    int it = 0;
#pragma unroll 1
    while (bad) {
#pragma unroll
        for (int i = 0; i < N; ++i) v[i] = ld_rlx(p + off(i));
        all1 = v[0].x; any1 = v[0].x;
#pragma unroll
        for (int i = 1; i < N; ++i) { all1 &= v[i].x; any1 |= v[i].x; }
        bad = (par ? ~all1 : any1) & 1u;
        if (++it > SPIN_LIMIT) { DIE(); break; }
    }
    __syncwarp();
}
__device__ __forceinline__ uint4 lds128(uint32_t a) {
    uint4 v;
    asm volatile("ld.shared.v4.u32 {%0,%1,%2,%3}, [%4];" : "=r"(v.x), "=r"(v.y), "=r"(v.z), "=r"(v.w) : "r"(a) : "memory");
    return v;
}
__device__ __forceinline__ void sts128(uint32_t a, uint32_t x, uint32_t y, uint32_t z, uint32_t w) {
    asm volatile("st.shared.v4.u32 [%0], {%1,%2,%3,%4};" ::"r"(a), "r"(x), "r"(y), "r"(z), "r"(w) : "memory");
}
__device__ __forceinline__ uint32_t pack2(float lo, float hi) {
    uint32_t d;
    asm("cvt.rn.bf16x2.f32 %0, %1, %2;" : "=r"(d) : "f"(hi), "f"(lo));
    return d;
}
__device__ __forceinline__ float bf_lo(uint32_t x) { return __uint_as_float(x << 16); }
__device__ __forceinline__ float bf_hi(uint32_t x) { return __uint_as_float(x & 0xffff0000u); }
__device__ __forceinline__ uint32_t hfma2(uint32_t a, uint32_t b, uint32_t c) {
    uint32_t d;
    asm("fma.rn.bf16x2 %0, %1, %2, %3;" : "=r"(d) : "r"(a), "r"(b), "r"(c));
    return d;
}
__device__ __forceinline__ uint32_t hmul2(uint32_t a, uint32_t b) {
    uint32_t d;
    asm("mul.rn.bf16x2 %0, %1, %2;" : "=r"(d) : "r"(a), "r"(b));
    return d;
}
__device__ __forceinline__ float ex2f(float x) {
    float y;
    asm("ex2.approx.ftz.f32 %0, %1;" : "=f"(y) : "f"(x));
    return y;
}
__device__ __forceinline__ uint32_t movmat(uint32_t a) {
    uint32_t d;
    asm volatile("movmatrix.sync.aligned.m8n8.trans.b16 %0, %1;" : "=r"(d) : "r"(a));
    return d;
}
__device__ __forceinline__ void mma16816(float& d0, float& d1, float& d2, float& d3, uint32_t a0, uint32_t a1, uint32_t a2,
                                         uint32_t a3, uint32_t b0, uint32_t b1, float c0, float c1, float c2, float c3) {
    asm("mma.sync.aligned.m16n8k16.row.col.f32.bf16.bf16.f32 {%0,%1,%2,%3}, {%4,%5,%6,%7}, {%8,%9}, {%10,%11,%12,%13};"
        : "=f"(d0), "=f"(d1), "=f"(d2), "=f"(d3)
        : "r"(a0), "r"(a1), "r"(a2), "r"(a3), "r"(b0), "r"(b1), "f"(c0), "f"(c1), "f"(c2), "f"(c3));
}
#define WG_FENCE() asm volatile("wgmma.fence.sync.aligned;" ::: "memory")
#define WG_COMMIT() asm volatile("wgmma.commit_group.sync.aligned;" ::: "memory")
#define WG_WAIT(n) asm volatile("wgmma.wait_group.sync.aligned %0;" ::"n"(n) : "memory")

__device__ __forceinline__ constexpr uint64_t bdesc(uint32_t addr) {
    return (uint64_t)(((addr & 0x3FFFFu) >> 4) | (512u << 16)) | ((uint64_t)(64u | (1u << 30)) << 32);
}

#define ACC8(d, o) "+f"(d[o]), "+f"(d[o + 1]), "+f"(d[o + 2]), "+f"(d[o + 3]), "+f"(d[o + 4]), "+f"(d[o + 5]), "+f"(d[o + 6]), "+f"(d[o + 7])
template <int SC>
__device__ __forceinline__ void wgmma128(float (&d)[64], const uint4& a, uint64_t db) {
    asm volatile(
        "wgmma.mma_async.sync.aligned.m64n128k16.f32.bf16.bf16 "
        "{%0,%1,%2,%3,%4,%5,%6,%7,%8,%9,%10,%11,%12,%13,%14,%15,%16,%17,%18,%19,%20,%21,%22,%23,%24,%25,%26,%27,%28,%29,%30,%31,"
        "%32,%33,%34,%35,%36,%37,%38,%39,%40,%41,%42,%43,%44,%45,%46,%47,%48,%49,%50,%51,%52,%53,%54,%55,%56,%57,%58,%59,%60,%61,%62,%63},"
        "{%64,%65,%66,%67}, %68, %69, 1, 1, 1;"
        : ACC8(d, 0), ACC8(d, 8), ACC8(d, 16), ACC8(d, 24), ACC8(d, 32), ACC8(d, 40), ACC8(d, 48), ACC8(d, 56)
        : "r"(a.x), "r"(a.y), "r"(a.z), "r"(a.w), "l"(db), "n"(SC));
}
template <int SC>
__device__ __forceinline__ void wgmma64(float (&d)[32], const uint4& a, uint64_t db) {
    asm volatile(
        "wgmma.mma_async.sync.aligned.m64n64k16.f32.bf16.bf16 "
        "{%0,%1,%2,%3,%4,%5,%6,%7,%8,%9,%10,%11,%12,%13,%14,%15,%16,%17,%18,%19,%20,%21,%22,%23,%24,%25,%26,%27,%28,%29,%30,%31},"
        "{%32,%33,%34,%35}, %36, %37, 1, 1, 1;"
        : ACC8(d, 0), ACC8(d, 8), ACC8(d, 16), ACC8(d, 24)
        : "r"(a.x), "r"(a.y), "r"(a.z), "r"(a.w), "l"(db), "n"(SC));
}
template <int SC>
__device__ __forceinline__ void wgmma48(float (&d)[24], const uint4& a, uint64_t db) {
    asm volatile(
        "wgmma.mma_async.sync.aligned.m64n48k16.f32.bf16.bf16 "
        "{%0,%1,%2,%3,%4,%5,%6,%7,%8,%9,%10,%11,%12,%13,%14,%15,%16,%17,%18,%19,%20,%21,%22,%23},"
        "{%24,%25,%26,%27}, %28, %29, 1, 1, 1;"
        : ACC8(d, 0), ACC8(d, 8), ACC8(d, 16)
        : "r"(a.x), "r"(a.y), "r"(a.z), "r"(a.w), "l"(db), "n"(SC));
}

struct LnC { uint32_t rh0, rl0, nm0, rh1, rl1, nm1; };
__device__ __forceinline__ void ln_set(float rs, float nm, uint32_t& rh, uint32_t& rl, uint32_t& nmp) {
    rh = pack2(rs, rs);
    const float lo = rs - bf_lo(rh);
    rl = pack2(lo, lo);
    nmp = pack2(nm, nm);
}
__device__ __forceinline__ void ln_mod(uint4& a, uint4 cs, const LnC& c) {
    a.x = hfma2(hfma2(a.x, c.rh0, hfma2(a.x, c.rl0, c.nm0)), cs.x, cs.z);
    a.y = hfma2(hfma2(a.y, c.rh1, hfma2(a.y, c.rl1, c.nm1)), cs.x, cs.z);
    a.z = hfma2(hfma2(a.z, c.rh0, hfma2(a.z, c.rl0, c.nm0)), cs.y, cs.w);
    a.w = hfma2(hfma2(a.w, c.rh1, hfma2(a.w, c.rl1, c.nm1)), cs.y, cs.w);
}
__device__ __forceinline__ float silu_bf(float c) {
    float s = __fdividef(c, 1.0f + __expf(-c));
    return bf_lo(pack2(s, s));
}
__device__ __forceinline__ void fma8(float* a, float s, uint4 w) {
    a[0] = fmaf(s, bf_lo(w.x), a[0]); a[1] = fmaf(s, bf_hi(w.x), a[1]);
    a[2] = fmaf(s, bf_lo(w.y), a[2]); a[3] = fmaf(s, bf_hi(w.y), a[3]);
    a[4] = fmaf(s, bf_lo(w.z), a[4]); a[5] = fmaf(s, bf_hi(w.z), a[5]);
    a[6] = fmaf(s, bf_lo(w.w), a[6]); a[7] = fmaf(s, bf_hi(w.w), a[7]);
}
__device__ __forceinline__ void red8(float* a, int lane) {
    const bool u16 = lane & 16, u8 = lane & 8, u4 = lane & 4;
#pragma unroll
    for (int k = 0; k < 4; ++k) {
        float keep = u16 ? a[k + 4] : a[k], send = u16 ? a[k] : a[k + 4];
        a[k] = keep + __shfl_xor_sync(~0u, send, 16);
    }
#pragma unroll
    for (int k = 0; k < 2; ++k) {
        float keep = u8 ? a[k + 2] : a[k], send = u8 ? a[k] : a[k + 2];
        a[k] = keep + __shfl_xor_sync(~0u, send, 8);
    }
    float keep = u4 ? a[1] : a[0], send = u4 ? a[0] : a[1];
    a[0] = keep + __shfl_xor_sync(~0u, send, 4);
}
__device__ __forceinline__ float sum8(uint4 v) {
    return ((bf_lo(v.x) + bf_hi(v.x)) + (bf_lo(v.y) + bf_hi(v.y))) + ((bf_lo(v.z) + bf_hi(v.z)) + (bf_lo(v.w) + bf_hi(v.w)));
}
__device__ __forceinline__ float sq2(uint32_t v, float m, float acc) {
    float a = bf_lo(v) - m, b = bf_hi(v) - m;
    return fmaf(a, a, fmaf(b, b, acc));
}
__device__ __forceinline__ uint32_t one_plus(uint32_t v) { return pack2(1.0f + bf_lo(v), 1.0f + bf_hi(v)); }

__device__ __forceinline__ constexpr int wpos(int m) { return m % NSTAGE; }
__device__ __forceinline__ constexpr int wpar(int m) { return ((m % NSTAGE == 4 ? 2 : 1) + m / NSTAGE) & 1; }
__device__ __forceinline__ float u2f(uint32_t v) { return __uint_as_float(v); }
__device__ __forceinline__ uint32_t f2u(float v) { return __float_as_uint(v); }

__global__ void __launch_bounds__(384, 1)
fused_kernel(const __grid_constant__ CUtensorMap tmQKV, const __grid_constant__ CUtensorMap tmWo,
             const __grid_constant__ CUtensorMap tmG, const __grid_constant__ CUtensorMap tmU,
             const __grid_constant__ CUtensorMap tmD, const __nv_bfloat16* __restrict__ x,
             const __nv_bfloat16* __restrict__ wo, const __nv_bfloat16* __restrict__ wg, const __nv_bfloat16* __restrict__ wu,
             const __nv_bfloat16* __restrict__ wd, const __nv_bfloat16* __restrict__ cvec,
             const __nv_bfloat16* __restrict__ wmod, __nv_bfloat16* __restrict__ out) {
    extern __shared__ __align__(1024) unsigned char smem[];
    constexpr uint32_t sb = 1024;
    if (s2u(smem) != sb) { DIE(); return; }
    constexpr uint32_t bars = sb + BAR_OFF;
    const int bid = blockIdx.x;
    const int j = bid >> 3, r = bid & 7;
    const int lane = threadIdx.x & 31;
    const int warp = threadIdx.x >> 5;

    if (warp >= 8) {
        asm volatile("setmaxnreg.dec.sync.aligned.u32 40;");
        volatile unsigned* s_epoch = (volatile unsigned*)(smem + MISC_OFF);
        if (threadIdx.x == 288) {
            unsigned e;
            asm volatile("ld.relaxed.gpu.global.u32 %0, [%1];" : "=r"(e) : "l"(&g_epoch) : "memory");
            *s_epoch = e + 1;
        }
        if (warp == 8) {
            if (lane == 0) {
#pragma unroll 1
                for (int i = 0; i < NBAR; ++i) mbar_init(bars + 8 * i, (i >= B_EMPTY && i < B_HALO) ? 8 : 1);
                fence_async_smem();
            }
            __syncwarp();
            bar_arrive(0, 384);
            if (lane == 0) {
#pragma unroll 1
                for (int n = 0; n < 12; ++n) {
                    const int pos = n == 0 ? 4 : n == 1 ? 0 : n < 8 ? n + 3 : n - 7;
                    if (n == 11) mbar_wait(bars + 8 * (B_EMPTY + 4), 0);
                    const uint32_t fb = bars + 8 * (B_FULL + pos), dst = sb + pos * STAGE_BYTES;
                    mbar_expect(fb, STAGE_BYTES);
                    tma5d(dst, &tmQKV, (n < 8 ? 512 : 0) + 64 * r, n < 8 ? 2 * n : 4 * (n - 8), fb);
                    tma5d(dst + 8192, &tmQKV, (n < 8 ? 1024 : 0) + 64 * r, n < 8 ? 2 * n : 4 * (n - 8) + 2, fb);
                }
                PROF(0);
                prefetch_l2((const char*)wo + bid * 4096, 4096);
                prefetch_l2((const char*)wg + bid * 11008, 11008);
                prefetch_l2((const char*)wu + bid * 11008, 11008);
                prefetch_l2((const char*)wd + bid * 11008, 11008);
                int pos = 0, rnd = 0;
#pragma unroll 1
                for (int m = 0; m < 40; ++m) {
                    mbar_wait(bars + 8 * (B_EMPTY + pos), ((pos == 4 ? 1 : 0) + rnd) & 1);
                    const uint32_t fb = bars + 8 * (B_FULL + pos), dst = sb + pos * STAGE_BYTES;
                    mbar_expect(fb, STAGE_BYTES);
                    if (m < 4) {
                        tma2d(dst, &tmWo, 64 * r, 128 * m, fb);
                        tma2d(dst + 8192, &tmWo, 64 * r, 128 * m + 64, fb);
                    } else if (m < 28) {
                        const int mm = m - 4, p = mm >> 3, rr = mm & 7;
                        tma2d(dst, &tmG, 176 * r + 64 * p, 64 * rr, fb);
                        tma2d(dst + 8192, &tmU, 176 * r + 64 * p, 64 * rr, fb);
                    } else {
                        const int mm = m - 28, cb = mm / 3, p = mm - 3 * cb;
                        const int col = 64 * ((r + 2 + 2 * cb) & 7), row = 352 * (r >> 1) + 64 * p;
                        tma2d(dst, &tmD, col, row, fb);
                        tma2d(dst + 8192, &tmD, col, row + 176, fb);
                    }
                    if (++pos == NSTAGE) { pos = 0; ++rnd; }
                }
            }
        } else {
            __syncwarp();
            bar_sync(0, 384);
            const unsigned epoch = *s_epoch;
            if (warp == 9) {
                if (lane == 0) {
                    if (j < 15) {
                        uint4* dst = g_kv + (size_t)bid * 2048;
#pragma unroll 1
                        for (int h = 0; h < 4; ++h) {
                            mbar_wait(bars + 8 * (B_KVW + h), 0);
                            bulk_s2g(dst + h * 512, sb + KV_OFF + h * 24576 + 16384, 8192);
                            asm volatile("cp.async.bulk.commit_group;" ::: "memory");
                        }
                        unsigned* fl = (unsigned*)&g_kvflag[bid * 2];
                        asm volatile("cp.async.bulk.wait_group 3;" ::: "memory");
                        asm volatile("st.relaxed.gpu.global.u32 [%0], %1;" ::"l"(fl + 0), "r"(epoch) : "memory");
                        PROF(1);
                        asm volatile("cp.async.bulk.wait_group 2;" ::: "memory");
                        asm volatile("st.relaxed.gpu.global.u32 [%0], %1;" ::"l"(fl + 1), "r"(epoch) : "memory");
                        asm volatile("cp.async.bulk.wait_group 1;" ::: "memory");
                        asm volatile("st.relaxed.gpu.global.u32 [%0], %1;" ::"l"(fl + 2), "r"(epoch) : "memory");
                        asm volatile("cp.async.bulk.wait_group 0;" ::: "memory");
                        asm volatile("st.relaxed.gpu.global.u32 [%0], %1;" ::"l"(fl + 3), "r"(epoch) : "memory");
                    }
                    mbar_arrive(bars + 8 * B_PUB);
                }
                PROF(2);
            } else if (warp == 10) {
                const int nn = j < 2 ? j : 2;
                const uint4* fl = &g_kvflag[(bid - 8 * (lane + 1)) * 2];
                uint4 f = make_uint4(epoch, epoch, epoch, epoch);
                if (lane < nn) f = ld_rlx(fl);
                mbar_wait(bars + 8 * B_KVW, 0);
                int h = 0, it = 0;
#pragma unroll 1
                while (true) {
                    int cnt = f.x != epoch ? 0 : f.y != epoch ? 1 : f.z != epoch ? 2 : f.w != epoch ? 3 : 4;
                    cnt = min(cnt, __shfl_xor_sync(~0u, cnt, 1));
                    cnt = __shfl_sync(~0u, cnt, 0);
                    if (lane == 0 && cnt > h) {
                        fence_async_all();
#pragma unroll 1
                        for (int hh = h; hh < cnt; ++hh) {
                            const uint32_t hb = bars + 8 * (B_HALO + hh);
                            mbar_expect(hb, nn * 8192);
#pragma unroll 1
                            for (int n = 1; n <= nn; ++n)
                                bulk_g2s(sb + KV_OFF + hh * 24576 + (2 - n) * 8192, g_kv + (size_t)(bid - 8 * n) * 2048 + hh * 512, 8192, hb);
                        }
                        if (h == 0) PROF(1);
                    }
                    h = max(h, cnt);
                    if (h == 4) break;
                    if (++it > SPIN_LIMIT) { DIE(); break; }
                    if (lane < nn) f = ld_rlx(fl);
                }
                PROF(2);
            } else {
                const uint32_t par = epoch & 1u;
                mbar_wait(bars + 8 * (B_FULL + 10), 0);
                {
                    const int half = lane & 1, rg = lane >> 1;
                    float a[8];
#pragma unroll
                    for (int k = 0; k < 8; ++k) a[k] = 0.f;
#pragma unroll 1
                    for (int b = 0; b < 8; ++b) {
                        const int row = b * 64 + rg * 4;
                        uint4 wv[4];
#pragma unroll
                        for (int i = 0; i < 4; ++i) wv[i] = ldg_nc(wmod + (size_t)(row + i) * 3072 + 1024 + 16 * bid + 8 * half);
                        const uint2 cv = *(const uint2*)(cvec + row);
                        fma8(a, silu_bf(bf_lo(cv.x)), wv[0]); fma8(a, silu_bf(bf_hi(cv.x)), wv[1]);
                        fma8(a, silu_bf(bf_lo(cv.y)), wv[2]); fma8(a, silu_bf(bf_hi(cv.y)), wv[3]);
                    }
                    red8(a, lane);
                    a[0] += __shfl_xor_sync(~0u, a[0], 2);
                    float* red2 = (float*)(smem + RED_OFF + 512);
                    if ((lane & 2) == 0) red2[half * 8 + (lane >> 2)] = a[0];
                    __syncwarp();
                    if (lane < 4) {
                        const uint4 v = *(const uint4*)(red2 + 4 * lane);
                        st_rlx(&g_m2[4 * bid + lane], tagw(v.x, par), v.y, v.z, v.w);
                    }
                }
                PROF(1);
                uint32_t* tab2 = (uint32_t*)(smem + TAB2_OFF);
#pragma unroll 1
                for (int q = 0; q < 9; ++q) {
                    const int e = q < 8 ? 128 + q * 32 + lane : (lane < 16 ? 16 * r + lane : 384 + 16 * r + (lane - 16));
                    uint4 v = ld_rlx(&g_m2[e]);
                    validate<1>(&v, &g_m2[e], [](int) { return 0; }, par);
                    uint32_t v0 = pack2(u2f(v.x), u2f(v.y)), v1 = pack2(u2f(v.z), u2f(v.w));
                    if (q < 8) {
                        const int ep = (q & 3) * 64 + lane * 2;
                        const int isc = q >> 2;
                        if (isc) { v0 = one_plus(v0); v1 = one_plus(v1); }
                        const int kap = ep >> 3, wi = ep & 7;
                        const int o0 = (kap * 4 + (wi & 3)) * 4 + (wi >> 2) + (isc ? 0 : 2);
                        tab2[o0] = v0;
                        tab2[o0 + 4] = v1;
                    } else {
                        *(float4*)(smem + GA_OFF + lane * 16) = make_float4(bf_lo(v0), bf_hi(v0), bf_lo(v1), bf_hi(v1));
                    }
                }
                __syncwarp();
                if (lane == 0) mbar_arrive(bars + 8 * B_TAB2);
                PROF(2);
            }
        }
    } else {
        const int w = warp, g = lane >> 2, t = lane & 3;
        const int row0 = 128 * j + 16 * w + g;
        uint4 A[32];
        LnC ln;
        const uint4* const xp = (const uint4*)x + (size_t)row0 * 64 + t;
#define LOADX(m) do { uint4 u0 = ldg_nc(xp + 4 * (m)), u1 = ldg_nc(xp + 512 + 4 * (m)); \
                      A[2 * (m)] = make_uint4(u0.x, u1.x, u0.y, u1.y); A[2 * (m) + 1] = make_uint4(u0.z, u1.z, u0.w, u1.w); } while (0)
        uint32_t par;
        {
            const int mrow = 256 * (bid & 1) + (threadIdx.x >> 1) * 2;
            const __nv_bfloat16* wp = wmod + (size_t)mrow * 3072 + 16 * (bid >> 1) + 8 * (lane & 1);
            const uint4 wv0 = ldg_nc(wp), wv1 = ldg_nc(wp + 3072);
            const uint32_t cv = __ldg((const uint32_t*)(cvec + mrow));
            const int srow = 128 * j + 16 * r + 2 * w + (lane >> 4);
            uint4 xs[4];
#pragma unroll
            for (int i = 0; i < 4; ++i) xs[i] = ldg_nc((const uint4*)x + (size_t)srow * 64 + i * 16 + (lane & 15));
            uint4 pv[4];
            pv[0] = ld_rlx(&g_m1[2 * threadIdx.x]); pv[1] = ld_rlx(&g_m1[2 * threadIdx.x + 1]);
            pv[2] = ld_rlx(&g_rs[row0]); pv[3] = ld_rlx(&g_rs[row0 + 8]);
            asm volatile("setmaxnreg.inc.sync.aligned.u32 232;");
            PROF(15);
            float a[8];
#pragma unroll
            for (int k = 0; k < 8; ++k) a[k] = 0.f;
            fma8(a, silu_bf(bf_lo(cv)), wv0);
            fma8(a, silu_bf(bf_hi(cv)), wv1);
            red8(a, lane);
            a[0] += __shfl_xor_sync(~0u, a[0], 2);
            float* red = (float*)(smem + RED_OFF);
            if ((lane & 2) == 0) red[w * 16 + (lane & 1) * 8 + (lane >> 2)] = a[0];
            PROF(16);
            bar_sync(0, 384);
            const unsigned epoch = *(volatile unsigned*)(smem + MISC_OFF);
            par = epoch & 1u;
            if (threadIdx.x < 4) {
                float4 v = *(const float4*)(red + 4 * threadIdx.x);
#pragma unroll
                for (int i = 1; i < 8; ++i) {
                    const float4 u = *(const float4*)(red + 16 * i + 4 * threadIdx.x);
                    v.x += u.x; v.y += u.y; v.z += u.z; v.w += u.w;
                }
                st_rlx(&g_m1[((bid >> 1) * 4 + threadIdx.x) * 2 + (bid & 1)], tagw(f2u(v.x), par), f2u(v.y), f2u(v.z), f2u(v.w));
            }
            float sm = (sum8(xs[0]) + sum8(xs[1])) + (sum8(xs[2]) + sum8(xs[3]));
#pragma unroll
            for (int o = 1; o < 16; o <<= 1) sm += __shfl_xor_sync(~0u, sm, o);
            const float mean = sm * (1.f / 512.f);
            float qa = 0.f, qb = 0.f;
#pragma unroll
            for (int i = 0; i < 4; ++i) { qa = sq2(xs[i].x, mean, sq2(xs[i].y, mean, qa)); qb = sq2(xs[i].z, mean, sq2(xs[i].w, mean, qb)); }
            qa += qb;
#pragma unroll
            for (int o = 1; o < 16; o <<= 1) qa += __shfl_xor_sync(~0u, qa, o);
            const float rstd = rsqrtf(qa * (1.f / 512.f) + 1e-5f);
            if ((lane & 15) == 0) st_rlx(&g_rs[srow], tagw(f2u(rstd), par), f2u(-mean * rstd), 0u, 0u);
            PROF(0);
#pragma unroll
            for (int m = 0; m < NX0; ++m) LOADX(m);
            validate<2>(pv, &g_m1[2 * threadIdx.x], [](int i) { return i; }, par);
            validate<2>(pv + 2, &g_rs[row0], [](int i) { return 8 * i; }, par);
            ln_set(u2f(pv[2].x), u2f(pv[2].y), ln.rh0, ln.rl0, ln.nm0);
            ln_set(u2f(pv[3].x), u2f(pv[3].y), ln.rh1, ln.rl1, ln.nm1);
            const int i = threadIdx.x & 127, isc = threadIdx.x >> 7;
            const int m = i >> 3, tt = (i >> 1) & 3, p = i & 1;
            uint32_t v0 = pack2(u2f(pv[0].x) + u2f(pv[1].x), u2f(pv[0].y) + u2f(pv[1].y));
            uint32_t v1 = pack2(u2f(pv[0].z) + u2f(pv[1].z), u2f(pv[0].w) + u2f(pv[1].w));
            if (isc) { v0 = one_plus(v0); v1 = one_plus(v1); }
            *(uint2*)(smem + TAB1_OFF + ((2 * m + p) * 4 + tt) * 16 + (isc ? 0 : 8)) = make_uint2(v0, v1);
#pragma unroll
            for (int m = NX0; m < 16; ++m) LOADX(m);
            bar_sync(1, 256);
            if (bid == 0 && threadIdx.x == 0)
                asm volatile("st.relaxed.gpu.global.u32 [%0], %1;" ::"l"(&g_epoch), "r"(epoch) : "memory");
        }
        PROF(1);

        uint32_t qf[16];
        {
            uint32_t kv[32];
            {
                float acc[64];
#pragma unroll
                for (int kb = 0; kb < 8; ++kb) {
                    const int pos = kb == 0 ? 4 : kb == 1 ? 0 : kb + 3;
#pragma unroll
                    for (int s = 0; s < 4; ++s) ln_mod(A[4 * kb + s], lds128(sb + TAB1_OFF + ((4 * kb + s) * 4 + t) * 16), ln);
                    mbar_wait(bars + 8 * (B_FULL + pos), 0);
                    const uint64_t d = bdesc(sb + pos * STAGE_BYTES);
                    WG_FENCE();
#pragma unroll
                    for (int s = 0; s < 4; ++s) {
                        if (kb == 0 && s == 0) wgmma128<0>(acc, A[4 * kb + s], d);
                        else wgmma128<1>(acc, A[4 * kb + s], d + s * 128);
                    }
                    WG_COMMIT();
                    if (kb == 2) {
                        WG_WAIT(2);
                        if (lane == 0) mbar_arrive(bars + 8 * (B_EMPTY + 4));
                    }
                }
                WG_WAIT(0);
                PROF(2);
#pragma unroll
                for (int i = 0; i < 32; ++i) kv[i] = pack2(acc[2 * i], acc[2 * i + 1]);
            }
            float accq[32];
            const uint32_t kvw = sb + KV_OFF + (16 + w) * 1024 + lane * 16;
#pragma unroll
            for (int h = 0; h < 4; ++h) {
                mbar_wait(bars + 8 * (B_FULL + 1 + h), h == 3 ? 1 : 0);
                const uint64_t d = bdesc(sb + (1 + h) * STAGE_BYTES);
                WG_FENCE();
#pragma unroll
                for (int s = 0; s < 8; ++s) {
                    if (h == 0 && s == 0) wgmma64<0>(accq, A[8 * h + s], d);
                    else wgmma64<1>(accq, A[8 * h + s], d + s * 128);
                }
                WG_COMMIT();
                if (h == 0) {
                    bar_sync(1, 256);
#pragma unroll
                    for (int hh = 0; hh < 4; ++hh) {
                        sts128(kvw + hh * 24576, kv[4 * hh], kv[4 * hh + 2], kv[4 * hh + 1], kv[4 * hh + 3]);
                        sts128(kvw + hh * 24576 + 512, movmat(kv[16 + 4 * hh]), movmat(kv[16 + 4 * hh + 1]), movmat(kv[16 + 4 * hh + 2]),
                               movmat(kv[16 + 4 * hh + 3]));
                        if (j < 2) {
                            sts128(kvw + hh * 24576 - 16384, 0, 0, 0, 0);
                            sts128(kvw + hh * 24576 - 16384 + 512, 0, 0, 0, 0);
                            if (j == 0) {
                                sts128(kvw + hh * 24576 - 8192, 0, 0, 0, 0);
                                sts128(kvw + hh * 24576 - 8192 + 512, 0, 0, 0, 0);
                            }
                        }
                        fence_async_smem();
                        __syncwarp();
                        if (lane == 0) mbar_arrive(bars + 8 * (B_KVW + hh));
                    }
                    PROF(17);
                }
            }
            WG_WAIT(0);
#pragma unroll
            for (int i = 0; i < 16; ++i) qf[i] = pack2(accq[2 * i], accq[2 * i + 1]);
        }
        PROF(3);
        uint4* const o_base = g_o + (size_t)(j * 8 + w) * 1024 + lane;
        uint4* const x1_base = g_x1 + (size_t)(j * 8 + w) * 1024 + lane;
        uint4* const st_base = g_st + (size_t)(j * 8 + w) * 64;

        {
            const float CS = 0.25f * 1.4426950408889634f;
            const int nv = 16 - 8 * j - w;
            const uint32_t mD = ((2 * t <= g) ? 0xffffu : 0u) | ((2 * t + 1 <= g) ? 0xffff0000u : 0u);
#pragma unroll 1
            for (int h = 0; h < 4; ++h) {
                mbar_wait(bars + 8 * (B_KVW + h), 0);
                mbar_wait(bars + 8 * (B_HALO + h), 0);
                PROF(18 + h);
                const uint32_t kb = sb + KV_OFF + h * 24576 + w * 1024 + lane * 16;
                float S[16][8];
#pragma unroll
                for (int i = 1; i < 16; ++i) {
                    uint4 k = lds128(kb + i * 1024);
                    float bias = i >= nv ? 0.f : -1e30f;
                    mma16816(S[i][0], S[i][1], S[i][2], S[i][3], qf[0], qf[1], qf[2], qf[3], k.x, k.y, bias, bias, bias, bias);
                    mma16816(S[i][4], S[i][5], S[i][6], S[i][7], qf[0], qf[1], qf[2], qf[3], k.z, k.w, bias, bias, bias, bias);
                }
                {
                    float d[8], o[8];
                    uint4 k = lds128(kb + 16 * 1024);
                    mma16816(d[0], d[1], d[2], d[3], qf[0], qf[1], qf[2], qf[3], k.x, k.y, 0.f, 0.f, 0.f, 0.f);
                    mma16816(d[4], d[5], d[6], d[7], qf[0], qf[1], qf[2], qf[3], k.z, k.w, 0.f, 0.f, 0.f, 0.f);
                    k = lds128(kb);
                    float bias = 0 >= nv ? 0.f : -1e30f;
                    mma16816(o[0], o[1], o[2], o[3], qf[0], qf[1], qf[2], qf[3], k.x, k.y, bias, bias, bias, bias);
                    mma16816(o[4], o[5], o[6], o[7], qf[0], qf[1], qf[2], qf[3], k.z, k.w, bias, bias, bias, bias);
                    S[0][0] = (2 * t <= g) ? d[0] : o[0];
                    S[0][1] = (2 * t + 1 <= g) ? d[1] : o[1];
                    S[0][2] = d[2]; S[0][3] = d[3]; S[0][4] = o[4]; S[0][5] = o[5];
                    S[0][6] = (2 * t <= g) ? d[6] : o[6];
                    S[0][7] = (2 * t + 1 <= g) ? d[7] : o[7];
                }
                float m0a = fmaxf(S[0][0], S[0][1]), m0b = fmaxf(S[0][4], S[0][5]);
                float m1a = fmaxf(S[0][2], S[0][3]), m1b = fmaxf(S[0][6], S[0][7]);
#pragma unroll
                for (int i = 1; i < 16; ++i) {
                    m0a = fmaxf(m0a, fmaxf(S[i][0], S[i][1])); m0b = fmaxf(m0b, fmaxf(S[i][4], S[i][5]));
                    m1a = fmaxf(m1a, fmaxf(S[i][2], S[i][3])); m1b = fmaxf(m1b, fmaxf(S[i][6], S[i][7]));
                }
                float m0 = fmaxf(m0a, m0b), m1 = fmaxf(m1a, m1b);
                m0 = fmaxf(m0, __shfl_xor_sync(~0u, m0, 1)); m1 = fmaxf(m1, __shfl_xor_sync(~0u, m1, 1));
                m0 = fmaxf(m0, __shfl_xor_sync(~0u, m0, 2)); m1 = fmaxf(m1, __shfl_xor_sync(~0u, m1, 2));
                const float c0 = -m0 * CS, c1 = -m1 * CS;
                float O[8], l0 = 0.f, l1 = 0.f;
#pragma unroll
                for (int i = 0; i < 8; ++i) O[i] = 0.f;
#pragma unroll
                for (int i = 0; i < 16; ++i) {
                    float p0 = ex2f(fmaf(S[i][0], CS, c0)), p1 = ex2f(fmaf(S[i][1], CS, c0));
                    float p2 = ex2f(fmaf(S[i][2], CS, c1)), p3 = ex2f(fmaf(S[i][3], CS, c1));
                    float p4 = ex2f(fmaf(S[i][4], CS, c0)), p5 = ex2f(fmaf(S[i][5], CS, c0));
                    float p6 = ex2f(fmaf(S[i][6], CS, c1)), p7 = ex2f(fmaf(S[i][7], CS, c1));
                    l0 += (p0 + p1) + (p4 + p5);
                    l1 += (p2 + p3) + (p6 + p7);
                    uint32_t a0 = pack2(p0, p1), a1 = pack2(p2, p3), a2 = pack2(p4, p5), a3 = pack2(p6, p7);
                    uint4 v = lds128(kb + i * 1024 + 512);
                    if (i == 0) {
                        mma16816(O[0], O[1], O[2], O[3], a0 & ~mD, 0u, a2, a3 & ~mD, v.x, v.y, O[0], O[1], O[2], O[3]);
                        mma16816(O[4], O[5], O[6], O[7], a0 & ~mD, 0u, a2, a3 & ~mD, v.z, v.w, O[4], O[5], O[6], O[7]);
                        v = lds128(kb + 16 * 1024 + 512);
                        mma16816(O[0], O[1], O[2], O[3], a0 & mD, a1, 0u, a3 & mD, v.x, v.y, O[0], O[1], O[2], O[3]);
                        mma16816(O[4], O[5], O[6], O[7], a0 & mD, a1, 0u, a3 & mD, v.z, v.w, O[4], O[5], O[6], O[7]);
                    } else {
                        mma16816(O[0], O[1], O[2], O[3], a0, a1, a2, a3, v.x, v.y, O[0], O[1], O[2], O[3]);
                        mma16816(O[4], O[5], O[6], O[7], a0, a1, a2, a3, v.z, v.w, O[4], O[5], O[6], O[7]);
                    }
                }
                l0 += __shfl_xor_sync(~0u, l0, 1); l1 += __shfl_xor_sync(~0u, l1, 1);
                l0 += __shfl_xor_sync(~0u, l0, 2); l1 += __shfl_xor_sync(~0u, l1, 2);
                const float i0 = __fdividef(1.f, l0), i1 = __fdividef(1.f, l1);
#pragma unroll
                for (int i = 0; i < 12; ++i) qf[i] = qf[i + 4];
                st_rlx(o_base + (4 * r + h) * 32, tagw(pack2(O[0] * i0, O[1] * i0), par), pack2(O[2] * i1, O[3] * i1),
                       pack2(O[4] * i0, O[5] * i0), pack2(O[6] * i1, O[7] * i1));
                if (h == 0) {
                    st_rlx(o_base + (4 * r + 3) * 32, par ^ 1u, 0, 0, 0);
                    if (lane < 8) st_rlx(st_base + r * 8 + lane, par ^ 1u, 0, 0, 0);
                    if (lane < 6) mbar_arrive(bars + 8 * (B_EMPTY + lane));
                } else if (h == 1) {
                    mbar_wait(bars + 8 * B_PUB, 0);
                    if (lane < 2) mbar_arrive(bars + 8 * (B_EMPTY + 6 + lane));
                } else if (h == 2) {
                    if (lane == 0) mbar_arrive(bars + 8 * (B_EMPTY + 8));
                }
            }
        }
        PROF(4);

        uint32_t x1bits;
        {
#pragma unroll
            for (int h = 0; h < 4; ++h)
#pragma unroll
                for (int i = 0; i < 8; ++i) A[8 * h + i] = ld_rlx(o_base + (4 * i + h) * 32);
            uint32_t xr[16];
            {
                const uint32_t* xq = (const uint32_t*)(x + (size_t)row0 * 512 + 64 * r) + t;
#pragma unroll
                for (int b = 0; b < 8; ++b) { xr[2 * b] = __ldg(xq + 4 * b); xr[2 * b + 1] = __ldg(xq + 2048 + 4 * b); }
            }
            float acc[32];
#pragma unroll
            for (int m = 0; m < 4; ++m) mbar_wait(bars + 8 * (B_FULL + wpos(m)), wpar(m));
            const uint64_t d0 = bdesc(sb);
#pragma unroll
            for (int h = 0; h < 4; ++h) {
                validate<8>(&A[8 * h], o_base + h * 32, [](int i) { return 128 * i; }, par);
                WG_FENCE();
#pragma unroll
                for (int i = 0; i < 8; ++i) {
                    if (h == 0 && i == 0) wgmma64<0>(acc, A[8 * h + i], d0);
                    else wgmma64<1>(acc, A[8 * h + i], d0 + i * 512 + h * 128);
                }
                WG_COMMIT();
            }
            if (lane < 2) mbar_arrive(bars + 8 * (B_EMPTY + 9 + lane));
            mbar_wait(bars + 8 * B_TAB2, 0);
            WG_WAIT(0);
            PROF(5);
            float s0 = 0.f, s1 = 0.f, q0 = 0.f, q1 = 0.f;
            uint32_t xo[16];
#pragma unroll
            for (int b = 0; b < 8; ++b) {
                const float2 ga = *(const float2*)(smem + GA_OFF + (8 * b + 2 * t) * 4);
                uint32_t p0 = pack2(fmaf(ga.x, acc[4 * b], bf_lo(xr[2 * b])), fmaf(ga.y, acc[4 * b + 1], bf_hi(xr[2 * b])));
                uint32_t p1 = pack2(fmaf(ga.x, acc[4 * b + 2], bf_lo(xr[2 * b + 1])), fmaf(ga.y, acc[4 * b + 3], bf_hi(xr[2 * b + 1])));
                xo[2 * b] = p0; xo[2 * b + 1] = p1;
                float a = bf_lo(p0), c = bf_hi(p0), e = bf_lo(p1), f = bf_hi(p1);
                s0 += a + c; q0 = fmaf(a, a, fmaf(c, c, q0));
                s1 += e + f; q1 = fmaf(e, e, fmaf(f, f, q1));
            }
            s0 += __shfl_xor_sync(~0u, s0, 1); q0 += __shfl_xor_sync(~0u, q0, 1);
            s1 += __shfl_xor_sync(~0u, s1, 1); q1 += __shfl_xor_sync(~0u, q1, 1);
            s0 += __shfl_xor_sync(~0u, s0, 2); q0 += __shfl_xor_sync(~0u, q0, 2);
            s1 += __shfl_xor_sync(~0u, s1, 2); q1 += __shfl_xor_sync(~0u, q1, 2);
            if (t == 0) st_rlx(st_base + r * 8 + g, tagw(f2u(q0), par), f2u(s0), f2u(q1), f2u(s1));
#pragma unroll
            for (int i = 0; i < 4; ++i) st_rlx(x1_base + (4 * r + i) * 32, tagw(xo[4 * i], par), xo[4 * i + 1], xo[4 * i + 2], xo[4 * i + 3]);
            x1bits = (xo[0] & 1u) | ((xo[4] & 1u) << 1) | ((xo[8] & 1u) << 2) | ((xo[12] & 1u) << 3);
        }
        PROF(6);
        {
            uint4 sv[2];
            const uint4* sp = st_base + 16 * t + g;
            sv[0] = ld_rlx(sp); sv[1] = ld_rlx(sp + 8);
            validate<2>(sv, sp, [](int i) { return 8 * i; }, par);
#pragma unroll
            for (int i = 0; i < 32; ++i) A[i] = ld_rlx(x1_base + i * 32);
            float q0 = u2f(sv[0].x) + u2f(sv[1].x), s0 = u2f(sv[0].y) + u2f(sv[1].y);
            float q1 = u2f(sv[0].z) + u2f(sv[1].z), s1 = u2f(sv[0].w) + u2f(sv[1].w);
            s0 += __shfl_xor_sync(~0u, s0, 1); q0 += __shfl_xor_sync(~0u, q0, 1);
            s1 += __shfl_xor_sync(~0u, s1, 1); q1 += __shfl_xor_sync(~0u, q1, 1);
            s0 += __shfl_xor_sync(~0u, s0, 2); q0 += __shfl_xor_sync(~0u, q0, 2);
            s1 += __shfl_xor_sync(~0u, s1, 2); q1 += __shfl_xor_sync(~0u, q1, 2);
            const float mean0 = s0 * (1.f / 512.f), mean1 = s1 * (1.f / 512.f);
            const float rs0 = rsqrtf(fmaxf(q0 * (1.f / 512.f) - mean0 * mean0, 0.f) + 1e-5f);
            const float rs1 = rsqrtf(fmaxf(q1 * (1.f / 512.f) - mean1 * mean1, 0.f) + 1e-5f);
            ln_set(rs0, -mean0 * rs0, ln.rh0, ln.rl0, ln.nm0);
            ln_set(rs1, -mean1 * rs1, ln.rh1, ln.rl1, ln.nm1);
        }
        PROF(7);
        uint4* const hh_base = g_hh + (size_t)(j * 8 + w) * (8 * 11 * 32) + lane;
        uint4* const pt_base = g_part + (size_t)(j * 8 + w) * (8 * 12 * 32) + lane;
        {
            float acc[64];
#pragma unroll
            for (int p = 0; p < 2; ++p) {
#pragma unroll
                for (int i = 0; i < 8; ++i) {
                    const int m = 4 + 8 * p + i;
                    if (p == 0) {
                        validate<4>(&A[4 * i], x1_base + 128 * i, [](int c) { return 32 * c; }, par);
                        if (i == 2 && lane < 4) mbar_arrive(bars + 8 * (B_EMPTY + lane));
#pragma unroll
                        for (int c = 0; c < 4; ++c) ln_mod(A[4 * i + c], lds128(sb + TAB2_OFF + ((4 * i + c) * 4 + t) * 16), ln);
                    }
                    mbar_wait(bars + 8 * (B_FULL + wpos(m)), wpar(m));
                    const uint64_t d = bdesc(sb + wpos(m) * STAGE_BYTES);
                    WG_FENCE();
#pragma unroll
                    for (int c = 0; c < 4; ++c) {
                        if (i == 0 && c == 0) wgmma128<0>(acc, A[4 * i + c], d);
                        else wgmma128<1>(acc, A[4 * i + c], d + c * 128);
                    }
                    WG_COMMIT();
                    if (i > 0) {
                        WG_WAIT(1);
                        if (lane == 0) mbar_arrive(bars + 8 * (B_EMPTY + wpos(m - 1)));
                    }
                }
                WG_WAIT(0);
                if (lane == 0) mbar_arrive(bars + 8 * (B_EMPTY + wpos(4 + 8 * p + 7)));
#pragma unroll
                for (int c = 0; c < 4; ++c) {
                    uint32_t hv[4];
#pragma unroll
                    for (int e = 0; e < 4; ++e)
                        hv[e] = hmul2(pack2(acc[8 * c + 2 * e], acc[8 * c + 2 * e + 1]), pack2(acc[32 + 8 * c + 2 * e], acc[32 + 8 * c + 2 * e + 1]));
                    st_rlx(hh_base + (r * 11 + 4 * p + c) * 32, tagw(hv[0], par), hv[1], hv[2], hv[3]);
                }
                PROF(8 + p);
            }
        }
        {
            float ag[24], au[24];
#pragma unroll
            for (int i = 0; i < 8; ++i) {
                const int m = 20 + i;
                mbar_wait(bars + 8 * (B_FULL + wpos(m)), wpar(m));
                const uint64_t d = bdesc(sb + wpos(m) * STAGE_BYTES);
                WG_FENCE();
#pragma unroll
                for (int c = 0; c < 4; ++c) {
                    if (i == 0 && c == 0) {
                        wgmma48<0>(ag, A[4 * i + c], d);
                        wgmma48<0>(au, A[4 * i + c], d + 512);
                    } else {
                        wgmma48<1>(ag, A[4 * i + c], d + c * 128);
                        wgmma48<1>(au, A[4 * i + c], d + 512 + c * 128);
                    }
                }
                WG_COMMIT();
                if (i == 0) {
#pragma unroll
                    for (int c = 0; c < 3; ++c) st_rlx(hh_base + (r * 11 + 8 + c) * 32, par ^ 1u, 0, 0, 0);
#pragma unroll
                    for (int c = 0; c < 4; ++c) st_rlx(pt_base + (((r + 6) & 7) * 12 + 8 + c) * 32, par ^ 1u, 0, 0, 0);
                } else {
                    WG_WAIT(1);
                    if (lane == 0) mbar_arrive(bars + 8 * (B_EMPTY + wpos(m - 1)));
                }
            }
            WG_WAIT(0);
            if (lane == 0) mbar_arrive(bars + 8 * (B_EMPTY + wpos(27)));
#pragma unroll
            for (int c = 0; c < 3; ++c) {
                uint32_t hv[4];
#pragma unroll
                for (int e = 0; e < 4; ++e)
                    hv[e] = hmul2(pack2(ag[8 * c + 2 * e], ag[8 * c + 2 * e + 1]), pack2(au[8 * c + 2 * e], au[8 * c + 2 * e + 1]));
                st_rlx(hh_base + (r * 11 + 8 + c) * 32, tagw(hv[0], par), hv[1], hv[2], hv[3]);
            }
        }
        PROF(10);
        {
            const uint4* const hp = hh_base + (r & 6) * 11 * 32;
            auto off8 = [](int k) { return ((k >> 2) * 11 + (k & 3)) * 32; };
            auto off6 = [](int k) { return ((k / 3) * 11 + (k % 3)) * 32; };
#pragma unroll
            for (int k = 0; k < 8; ++k) A[k] = ld_rlx(hp + off8(k));
#pragma unroll
            for (int k = 0; k < 8; ++k) A[8 + k] = ld_rlx(hp + 128 + off8(k));
#pragma unroll
            for (int k = 0; k < 6; ++k) A[16 + k] = ld_rlx(hp + 256 + off6(k));
            float acc[2][32];
            uint4 P[12], X1[4];
#pragma unroll
            for (int cb = 0; cb < 4; ++cb) {
#pragma unroll
                for (int p = 0; p < 3; ++p) {
                    const int m = 28 + 3 * cb + p;
                    if (cb == 0) {
                        if (p < 2) validate<8>(&A[8 * p], hp + 128 * p, off8, par);
                        else validate<6>(&A[16], hp + 256, off6, par);
                    }
                    mbar_wait(bars + 8 * (B_FULL + wpos(m)), wpar(m));
                    const uint64_t d = bdesc(sb + wpos(m) * STAGE_BYTES);
                    WG_FENCE();
                    if (p < 2) {
#pragma unroll
                        for (int k = 0; k < 8; ++k) {
                            if (p == 0 && k == 0) wgmma64<0>(acc[cb & 1], A[8 * p + k], d);
                            else wgmma64<1>(acc[cb & 1], A[8 * p + k], d + k * 128);
                        }
                    } else {
#pragma unroll
                        for (int k = 0; k < 6; ++k) wgmma64<1>(acc[cb & 1], A[16 + k], d + ((k / 3) * 4 + k % 3) * 128);
                    }
                    WG_COMMIT();
                    if (cb == 0 && p == 1) {
                        WG_WAIT(1);
                        if (lane == 0) mbar_arrive(bars + 8 * (B_EMPTY + wpos(28)));
                    }
                    if (cb > 0 && p == 0) {
                        WG_WAIT(1);
                        const float* a = acc[(cb - 1) & 1];
                        uint4* dst = pt_base + (((r + 2 * cb) & 7) * 12 + 4 * (cb - 1)) * 32;
#pragma unroll
                        for (int c = 0; c < 4; ++c)
                            st_rlx(dst + c * 32, tagw(pack2(a[8 * c], a[8 * c + 1]), par), pack2(a[8 * c + 2], a[8 * c + 3]),
                                   pack2(a[8 * c + 4], a[8 * c + 5]), pack2(a[8 * c + 6], a[8 * c + 7]));
                    }
                    if (cb == 3 && p == 1) {
#pragma unroll
                        for (int i = 0; i < 4; ++i) X1[i] = ld_rlx(x1_base + (4 * r + i) * 32);
#pragma unroll
                        for (int i = 0; i < 8; ++i) P[i] = ld_rlx(pt_base + (r * 12 + i) * 32);
                    }
                }
            }
#pragma unroll
            for (int i = 8; i < 12; ++i) P[i] = ld_rlx(pt_base + (r * 12 + i) * 32);
            validate<8>(P, pt_base + r * 12 * 32, [](int i) { return 32 * i; }, par);
            WG_WAIT(0);
            PROF(11);
            validate<4>(P + 8, pt_base + (r * 12 + 8) * 32, [](int i) { return 32 * i; }, par);
            PROF(13);
#pragma unroll
            for (int i = 0; i < 4; ++i) {
                const uint32_t xw[4] = {(X1[i].x & ~1u) | ((x1bits >> i) & 1u), X1[i].y, X1[i].z, X1[i].w};
                const uint32_t pa[4] = {P[i].x, P[i].y, P[i].z, P[i].w}, pb[4] = {P[4 + i].x, P[4 + i].y, P[4 + i].z, P[4 + i].w},
                               pc[4] = {P[8 + i].x, P[8 + i].y, P[8 + i].z, P[8 + i].w};
                uint32_t o[4];
#pragma unroll
                for (int e = 0; e < 4; ++e) {
                    const float2 gb = *(const float2*)(smem + GB_OFF + (16 * i + 8 * (e >> 1) + 2 * t) * 4);
                    const float y0 = (acc[1][8 * i + 2 * e] + bf_lo(pa[e])) + (bf_lo(pb[e]) + bf_lo(pc[e]));
                    const float y1 = (acc[1][8 * i + 2 * e + 1] + bf_hi(pa[e])) + (bf_hi(pb[e]) + bf_hi(pc[e]));
                    o[e] = pack2(fmaf(gb.x, y0, bf_lo(xw[e])), fmaf(gb.y, y1, bf_hi(xw[e])));
                }
                const bool t1 = t & 1, t2b = t & 2;
                uint32_t k0 = t1 ? o[1] : o[0], s0 = t1 ? o[0] : o[1];
                uint32_t k1 = t1 ? o[3] : o[2], s1 = t1 ? o[2] : o[3];
                s0 = __shfl_xor_sync(~0u, s0, 1); s1 = __shfl_xor_sync(~0u, s1, 1);
                uint32_t a0 = t1 ? s0 : k0, a1 = t1 ? k0 : s0;
                uint32_t b0 = t1 ? s1 : k1, b1 = t1 ? k1 : s1;
                uint32_t kk0 = t2b ? b0 : a0, kk1 = t2b ? b1 : a1, ss0 = t2b ? a0 : b0, ss1 = t2b ? a1 : b1;
                ss0 = __shfl_xor_sync(~0u, ss0, 2); ss1 = __shfl_xor_sync(~0u, ss1, 2);
                uint4 res = t2b ? make_uint4(ss0, ss1, kk0, kk1) : make_uint4(kk0, kk1, ss0, ss1);
                *(uint4*)(out + (size_t)(row0 + 8 * (t & 1)) * 512 + 64 * r + 16 * i + 8 * (t >> 1)) = res;
            }
        }
        PROF(12);
    }
}

typedef CUresult (*EncodeFn)(CUtensorMap*, CUtensorMapDataType, cuuint32_t, void*, const cuuint64_t*, const cuuint64_t*,
                             const cuuint32_t*, const cuuint32_t*, CUtensorMapInterleave, CUtensorMapSwizzle,
                             CUtensorMapL2promotion, CUtensorMapFloatOOBfill);

void make2d(EncodeFn enc, CUtensorMap* m, const void* p, uint64_t cols, uint64_t rows) {
    cuuint64_t dims[2] = {cols, rows};
    cuuint64_t str[1] = {cols * 2};
    cuuint32_t box[2] = {64, 64}, es[2] = {1, 1};
    enc(m, CU_TENSOR_MAP_DATA_TYPE_BFLOAT16, 2, (void*)p, dims, str, box, es, CU_TENSOR_MAP_INTERLEAVE_NONE,
        CU_TENSOR_MAP_SWIZZLE_128B, CU_TENSOR_MAP_L2_PROMOTION_L2_128B, CU_TENSOR_MAP_FLOAT_OOB_FILL_NONE);
}

}

extern "C" void kernel_launch(void* const* d_in, const int* in_sizes, int n_in, void* d_out, int out_size) {
    const __nv_bfloat16* x = (const __nv_bfloat16*)d_in[0];
    const __nv_bfloat16* wqkv = (const __nv_bfloat16*)d_in[1];
    const __nv_bfloat16* wo = (const __nv_bfloat16*)d_in[2];
    const __nv_bfloat16* wg = (const __nv_bfloat16*)d_in[4];
    const __nv_bfloat16* wu = (const __nv_bfloat16*)d_in[5];
    const __nv_bfloat16* wd = (const __nv_bfloat16*)d_in[6];
    const __nv_bfloat16* c = (const __nv_bfloat16*)d_in[7];
    const __nv_bfloat16* wmod = (const __nv_bfloat16*)d_in[8];

    void* fn = nullptr;
    cudaDriverEntryPointQueryResult qr;
    cudaGetDriverEntryPoint("cuTensorMapEncodeTiled", &fn, cudaEnableDefault, &qr);
    EncodeFn enc = (EncodeFn)fn;
    CUtensorMap tmQKV, tmWo, tmG, tmU, tmD;
    {
        cuuint64_t dims[5] = {1536, 2, 4, 4, 16};
        cuuint64_t str[4] = {3072, 8 * 3072, 2 * 3072, 32 * 3072};
        cuuint32_t box[5] = {64, 2, 4, 4, 2}, es[5] = {1, 1, 1, 1, 1};
        enc(&tmQKV, CU_TENSOR_MAP_DATA_TYPE_BFLOAT16, 5, (void*)wqkv, dims, str, box, es, CU_TENSOR_MAP_INTERLEAVE_NONE,
            CU_TENSOR_MAP_SWIZZLE_128B, CU_TENSOR_MAP_L2_PROMOTION_L2_128B, CU_TENSOR_MAP_FLOAT_OOB_FILL_NONE);
    }
    make2d(enc, &tmWo, wo, 512, 512);
    make2d(enc, &tmG, wg, 1376, 512);
    make2d(enc, &tmU, wu, 1376, 512);
    make2d(enc, &tmD, wd, 512, 1376);
    cudaFuncSetAttribute(fused_kernel, cudaFuncAttributeMaxDynamicSharedMemorySize, SMEM_BYTES);
    fused_kernel<<<128, 384, SMEM_BYTES, cudaStreamPerThread>>>(tmQKV, tmWo, tmG, tmU, tmD, x, wo, wg, wu, wd, c, wmod,
                                                               (__nv_bfloat16*)d_out);
}
```

```cpp
#include <cuda_runtime.h>
#include <cuda_bf16.h>
#include <cuda.h>
#include <stdint.h>

namespace {

constexpr int NSTAGE = 11;
constexpr int STAGE_BYTES = 16384;
constexpr int KV_OFF = 1 * STAGE_BYTES;
constexpr int OUT_OFF = NSTAGE * STAGE_BYTES;
constexpr int TAB1_OFF = OUT_OFF + 12288;
constexpr int TAB2_OFF = TAB1_OFF + 2048;
constexpr int GA_OFF = TAB2_OFF + 2048;
constexpr int GB_OFF = GA_OFF + 256;
constexpr int ONES_OFF = GB_OFF + 256;
constexpr int RED_OFF = ONES_OFF + 640;
constexpr int MISC_OFF = RED_OFF + 576;
constexpr int BAR_OFF = MISC_OFF + 64;
constexpr int B_FULL = 0, B_HALO = 11, B_TAB2 = 15, B_PUB = 16, B_XF = 18, B_HLD = 20;
constexpr int B_EMPTY = 24, B_KVW = 35, B_GO = 36, B_DONE = 37, NBAR = 38;
constexpr int SMEM_BYTES = BAR_OFF + NBAR * 8;

#define NSPEC 0
#define VCHK 2
#define PUBGAP 250
constexpr int SPIN_LIMIT = 1 << 21;
#define DIE() asm volatile("st.global.u32 [%0], %1;" ::"l"(0ull), "r"(0) : "memory")

__device__ uint4 g_kv[16 * 8 * 2048];
constexpr int X_O = 0, X_X1 = 32, X_HH = 64, X_PT = 160, X_XR = 256, X_ST = 288, X_ROWS = 290;
__device__ uint4 g_x[16 * 8 * X_ROWS * 32];
__device__ uint4 g_m1[512];
__device__ uint4 g_m2[512];
__device__ uint4 g_rs[2048];
__device__ unsigned g_cnt;
#define PROF(i) do {} while (0)
#define PROF_DUMP() do {} while (0)
#define PROF_EXTRA 0
#define PROF2(i) do {} while (0)

__device__ __forceinline__ uint32_t s2u(const void* p) { return (uint32_t)__cvta_generic_to_shared(p); }
__device__ __forceinline__ bool elect() {
    uint32_t p;
    asm volatile("{\n.reg .pred p;\nelect.sync _|p, 0xffffffff;\nselp.u32 %0, 1, 0, p;\n}" : "=r"(p));
    return p;
}
__device__ __forceinline__ void mbar_init(uint32_t b, int c) {
    asm volatile("mbarrier.init.shared::cta.b64 [%0], %1;" ::"r"(b), "r"(c) : "memory");
}
__device__ __forceinline__ void mbar_expect(uint32_t b, uint32_t bytes) {
    asm volatile("mbarrier.arrive.expect_tx.shared::cta.b64 _, [%0], %1;" ::"r"(b), "r"(bytes) : "memory");
}
__device__ __forceinline__ void mbar_arrive(uint32_t b) {
    asm volatile("mbarrier.arrive.shared::cta.b64 _, [%0];" ::"r"(b) : "memory");
}
__device__ __forceinline__ void mbar_arrive_lt(uint32_t b, int a, int n) {
    asm volatile("{\n.reg .pred p;\nsetp.lt.s32 p, %1, %2;\n@p mbarrier.arrive.shared::cta.b64 _, [%0];\n}" ::"r"(b), "r"(a), "r"(n) : "memory");
}
__device__ __forceinline__ void mbar_wait(uint32_t b, uint32_t ph) {
    asm volatile("{\n.reg .pred p;\nLOOP_%=:\nmbarrier.try_wait.parity.shared::cta.b64 p, [%0], %1;\n@!p bra LOOP_%=;\n}"
                 ::"r"(b), "r"(ph) : "memory");
}
__device__ __forceinline__ void mbar_wait_b(uint32_t b, uint32_t ph) {
    asm volatile(
        "{\n.reg .pred p;\n.reg .u32 n;\n"
        "mov.u32 n, 0;\n"
        "LOOP_%=:\n"
        "mbarrier.try_wait.parity.shared::cta.b64 p, [%0], %1;\n"
        "@p bra DONE_%=;\n"
        "add.u32 n, n, 1;\n"
        "setp.lt.u32 p, n, %2;\n"
        "@p bra LOOP_%=;\n"
        "st.global.u32 [%3], n;\n"
        "DONE_%=:\n}" ::"r"(b), "r"(ph), "n"(SPIN_LIMIT), "l"(0ull) : "memory");
}
__device__ __forceinline__ void bar_sync(int id, int n) { asm volatile("bar.sync %0, %1;" ::"r"(id), "r"(n) : "memory"); }
__device__ __forceinline__ void bar_arrive(int id, int n) { asm volatile("bar.arrive %0, %1;" ::"r"(id), "r"(n) : "memory"); }
__device__ __forceinline__ bool bar_or(bool v, int id) {
    uint32_t o;
    asm volatile("{\n.reg .pred p, q;\nsetp.ne.u32 p, %1, 0;\nbar.red.or.pred q, %2, 128, p;\nselp.u32 %0, 1, 0, q;\n}"
                 : "=r"(o) : "r"((uint32_t)v), "r"(id) : "memory");
    return o;
}
__device__ __forceinline__ void bar_sync_if(int c, int id, int n) {
    asm volatile("{\n.reg .pred p;\nsetp.ne.u32 p, %0, 0;\n@p bar.sync %1, %2;\n}" ::"r"(c), "r"(id), "r"(n) : "memory");
}
__device__ __forceinline__ void bar_arrive_if(int c, int id, int n) {
    asm volatile("{\n.reg .pred p;\nsetp.ne.u32 p, %0, 0;\n@p bar.arrive %1, %2;\n}" ::"r"(c), "r"(id), "r"(n) : "memory");
}
__device__ __forceinline__ void fence_async_smem() { asm volatile("fence.proxy.async.shared::cta;" ::: "memory"); }

__device__ __forceinline__ void tma2d(uint32_t dst, const CUtensorMap* m, int c0, int c1, uint32_t bar) {
    asm volatile("cp.async.bulk.tensor.2d.shared::cluster.global.mbarrier::complete_tx::bytes [%0], [%1, {%3, %4}], [%2];"
                 ::"r"(dst), "l"(m), "r"(bar), "r"(c0), "r"(c1) : "memory");
}
__device__ __forceinline__ void bulk_g2s(uint32_t dst, const void* src, uint32_t bytes, uint32_t bar) {
    asm volatile("cp.async.bulk.shared::cluster.global.mbarrier::complete_tx::bytes [%0], [%1], %2, [%3];"
                 ::"r"(dst), "l"(src), "r"(bytes), "r"(bar) : "memory");
}
__device__ __forceinline__ void bulk_s2g(void* dst, uint32_t src, uint32_t bytes) {
    asm volatile("cp.async.bulk.global.shared::cta.bulk_group [%0], [%1], %2;" ::"l"(dst), "r"(src), "r"(bytes) : "memory");
}
__device__ __forceinline__ void prefetch_l2(const void* p, uint32_t bytes) {
    asm volatile("cp.async.bulk.prefetch.L2.global [%0], %1;" ::"l"(p), "r"(bytes) : "memory");
}
__device__ __forceinline__ uint4 ldg_nc(const void* p) {
    uint4 v;
    asm volatile("ld.global.nc.v4.u32 {%0,%1,%2,%3}, [%4];" : "=r"(v.x), "=r"(v.y), "=r"(v.z), "=r"(v.w) : "l"(p));
    return v;
}
__device__ __forceinline__ unsigned ld_u32(const unsigned* p) {
    unsigned v;
    asm volatile("ld.relaxed.gpu.global.u32 %0, [%1];" : "=r"(v) : "l"(p) : "memory");
    return v;
}
__device__ __forceinline__ uint4 ld_rlx(const void* p) {
    uint4 v;
    asm volatile("ld.relaxed.gpu.global.v4.u32 {%0,%1,%2,%3}, [%4];" : "=r"(v.x), "=r"(v.y), "=r"(v.z), "=r"(v.w) : "l"(p) : "memory");
    return v;
}
__device__ __forceinline__ void st_rlx(void* p, uint32_t x, uint32_t y, uint32_t z, uint32_t w) {
    asm volatile("st.relaxed.gpu.global.v4.u32 [%0], {%1,%2,%3,%4};" ::"l"(p), "r"(x), "r"(y), "r"(z), "r"(w) : "memory");
}
__device__ __forceinline__ uint32_t tagw(uint32_t x, uint32_t par) {
    uint32_t d;
    asm("lop3.b32 %0, %1, 0xfffffffe, %2, 0xea;" : "=r"(d) : "r"(x), "r"(par));
    return d;
}
template <int N>
__device__ __forceinline__ bool stale(const uint4* v, uint32_t par) {
    uint32_t bad = 0;
#pragma unroll
    for (int i = 0; i < N; ++i) asm("lop3.b32 %0, %1, %2, %0, 0xbe;" : "+r"(bad) : "r"(v[i].x), "r"(par));
    return __any_sync(~0u, bad & 1u);
}
template <int N, class F>
__device__ __forceinline__ void poll(uint4* v, const uint4* p, F off, uint32_t par) {
#pragma unroll 1
    do {
#pragma unroll
        for (int i = 0; i < N; ++i) v[i] = ld_rlx(p + off(i));
    } while (stale<N>(v, par));
}
template <int N, class F>
__device__ __forceinline__ void validate(uint4* v, const uint4* p, F off, uint32_t par) {
    if (__builtin_expect(stale<N>(v, par), 0)) poll<N>(v, p, off, par);
}
__device__ __forceinline__ uint4 lds128(uint32_t a) {
    uint4 v;
    asm volatile("ld.shared.v4.u32 {%0,%1,%2,%3}, [%4];" : "=r"(v.x), "=r"(v.y), "=r"(v.z), "=r"(v.w) : "r"(a) : "memory");
    return v;
}
__device__ __forceinline__ void sts128(uint32_t a, uint32_t x, uint32_t y, uint32_t z, uint32_t w) {
    asm volatile("st.shared.v4.u32 [%0], {%1,%2,%3,%4};" ::"r"(a), "r"(x), "r"(y), "r"(z), "r"(w) : "memory");
}
__device__ __forceinline__ void stsm4(uint32_t a, uint32_t x, uint32_t y, uint32_t z, uint32_t w) {
    asm volatile("stmatrix.sync.aligned.m8n8.x4.shared.b16 [%0], {%1,%2,%3,%4};" ::"r"(a), "r"(x), "r"(y), "r"(z), "r"(w) : "memory");
}
__device__ __forceinline__ uint4 ldsm4(uint32_t a) {
    uint4 v;
    asm volatile("ldmatrix.sync.aligned.m8n8.x4.shared.b16 {%0,%1,%2,%3}, [%4];" : "=r"(v.x), "=r"(v.y), "=r"(v.z), "=r"(v.w) : "r"(a) : "memory");
    return v;
}
__device__ __forceinline__ uint4 ldsm4t(uint32_t a) {
    uint4 v;
    asm volatile("ldmatrix.sync.aligned.m8n8.x4.trans.shared.b16 {%0,%1,%2,%3}, [%4];" : "=r"(v.x), "=r"(v.y), "=r"(v.z), "=r"(v.w) : "r"(a) : "memory");
    return v;
}
template <int ACC, int NT = 2>
__device__ __forceinline__ void mma2(float* d, const uint4& a, const uint4& b) {
#pragma unroll
    for (int i = 0; i < NT; ++i)
        asm("mma.sync.aligned.m16n8k16.row.col.f32.bf16.bf16.f32 {%0,%1,%2,%3}, {%4,%5,%6,%7}, {%8,%9}, {%10,%11,%12,%13};"
            : "=f"(d[4 * i]), "=f"(d[4 * i + 1]), "=f"(d[4 * i + 2]), "=f"(d[4 * i + 3])
            : "r"(a.x), "r"(a.y), "r"(a.z), "r"(a.w), "r"(i ? b.z : b.x), "r"(i ? b.w : b.y), "f"(ACC ? d[4 * i] : 0.f),
              "f"(ACC ? d[4 * i + 1] : 0.f), "f"(ACC ? d[4 * i + 2] : 0.f), "f"(ACC ? d[4 * i + 3] : 0.f));
}
__device__ __forceinline__ uint32_t pack2(float lo, float hi) {
    uint32_t d;
    asm("cvt.rn.bf16x2.f32 %0, %1, %2;" : "=r"(d) : "f"(hi), "f"(lo));
    return d;
}
__device__ __forceinline__ uint4 pack8(const float* a) {
    return make_uint4(pack2(a[0], a[1]), pack2(a[2], a[3]), pack2(a[4], a[5]), pack2(a[6], a[7]));
}
__device__ __forceinline__ float bf_lo(uint32_t x) { return __uint_as_float(x << 16); }
__device__ __forceinline__ float bf_hi(uint32_t x) { return __uint_as_float(x & 0xffff0000u); }
__device__ __forceinline__ float u2f(uint32_t v) { return __uint_as_float(v); }
__device__ __forceinline__ uint32_t f2u(float v) { return __float_as_uint(v); }
__device__ __forceinline__ uint32_t hfma2(uint32_t a, uint32_t b, uint32_t c) {
    uint32_t d;
    asm("fma.rn.bf16x2 %0, %1, %2, %3;" : "=r"(d) : "r"(a), "r"(b), "r"(c));
    return d;
}
__device__ __forceinline__ uint32_t hmul2(uint32_t a, uint32_t b) {
    uint32_t d;
    asm("mul.rn.bf16x2 %0, %1, %2;" : "=r"(d) : "r"(a), "r"(b));
    return d;
}
__device__ __forceinline__ uint4 gate8(const float* a, const float* b) {
    const uint4 u = pack8(a), v = pack8(b);
    return make_uint4(hmul2(u.x, v.x), hmul2(u.y, v.y), hmul2(u.z, v.z), hmul2(u.w, v.w));
}
__device__ __forceinline__ float ex2f(float x) {
    float y;
    asm("ex2.approx.ftz.f32 %0, %1;" : "=f"(y) : "f"(x));
    return y;
}
__device__ __forceinline__ float rcpf(float x) {
    float y;
    asm("rcp.approx.ftz.f32 %0, %1;" : "=f"(y) : "f"(x));
    return y;
}
__device__ __forceinline__ float sqrtaf(float x) {
    float y;
    asm("sqrt.approx.ftz.f32 %0, %1;" : "=f"(y) : "f"(x));
    return y;
}
#define WG_FENCE() asm volatile("wgmma.fence.sync.aligned;" ::: "memory")
#define WG_COMMIT() asm volatile("wgmma.commit_group.sync.aligned;" ::: "memory")
#define WG_WAIT(n) asm volatile("wgmma.wait_group.sync.aligned %0;" ::"n"(n) : "memory")
template <int N>
__device__ __forceinline__ void pin(float* d) {
#pragma unroll
    for (int i = 0; i < N; ++i) asm volatile("" : "+f"(d[i])::"memory");
}

__device__ __forceinline__ uint64_t bdesc(uint32_t addr) {
    return (uint64_t)((addr >> 4) | (512u << 16)) | ((uint64_t)(64u | (1u << 30)) << 32);
}
__device__ __forceinline__ uint64_t cdesc(uint32_t addr, uint32_t lbo, uint32_t sbo) {
    return (uint64_t)((addr >> 4) | ((lbo >> 4) << 16)) | ((uint64_t)(sbo >> 4) << 32);
}
template <int SC>
__device__ __forceinline__ void wgmma128(float* d, const uint4& a, uint64_t db) {
    asm volatile("wgmma.mma_async.sync.aligned.m64n128k16.f32.bf16.bf16 {%0,%1,%2,%3,%4,%5,%6,%7,%8,%9,%10,%11,%12,%13,%14,%15,%16,%17,%18,%19,%20,%21,%22,%23,%24,%25,%26,%27,%28,%29,%30,%31,%32,%33,%34,%35,%36,%37,%38,%39,%40,%41,%42,%43,%44,%45,%46,%47,%48,%49,%50,%51,%52,%53,%54,%55,%56,%57,%58,%59,%60,%61,%62,%63}, "
                 "{%64,%65,%66,%67}, %68, %69, 1, 1, 1;"
                 : "+f"(d[0]), "+f"(d[1]), "+f"(d[2]), "+f"(d[3]), "+f"(d[4]), "+f"(d[5]), "+f"(d[6]), "+f"(d[7]), "+f"(d[8]), "+f"(d[9]), "+f"(d[10]), "+f"(d[11]), "+f"(d[12]), "+f"(d[13]), "+f"(d[14]), "+f"(d[15]), "+f"(d[16]), "+f"(d[17]), "+f"(d[18]), "+f"(d[19]), "+f"(d[20]), "+f"(d[21]), "+f"(d[22]), "+f"(d[23]), "+f"(d[24]), "+f"(d[25]), "+f"(d[26]), "+f"(d[27]), "+f"(d[28]), "+f"(d[29]), "+f"(d[30]), "+f"(d[31]), "+f"(d[32]), "+f"(d[33]), "+f"(d[34]), "+f"(d[35]), "+f"(d[36]), "+f"(d[37]), "+f"(d[38]), "+f"(d[39]), "+f"(d[40]), "+f"(d[41]), "+f"(d[42]), "+f"(d[43]), "+f"(d[44]), "+f"(d[45]), "+f"(d[46]), "+f"(d[47]), "+f"(d[48]), "+f"(d[49]), "+f"(d[50]), "+f"(d[51]), "+f"(d[52]), "+f"(d[53]), "+f"(d[54]), "+f"(d[55]), "+f"(d[56]), "+f"(d[57]), "+f"(d[58]), "+f"(d[59]), "+f"(d[60]), "+f"(d[61]), "+f"(d[62]), "+f"(d[63])
                 : "r"(a.x), "r"(a.y), "r"(a.z), "r"(a.w), "l"(db), "n"(SC));
}
template <int SC>
__device__ __forceinline__ void wgmma64(float* d, const uint4& a, uint64_t db) {
    asm volatile("wgmma.mma_async.sync.aligned.m64n64k16.f32.bf16.bf16 {%0,%1,%2,%3,%4,%5,%6,%7,%8,%9,%10,%11,%12,%13,%14,%15,%16,%17,%18,%19,%20,%21,%22,%23,%24,%25,%26,%27,%28,%29,%30,%31}, "
                 "{%32,%33,%34,%35}, %36, %37, 1, 1, 1;"
                 : "+f"(d[0]), "+f"(d[1]), "+f"(d[2]), "+f"(d[3]), "+f"(d[4]), "+f"(d[5]), "+f"(d[6]), "+f"(d[7]), "+f"(d[8]), "+f"(d[9]), "+f"(d[10]), "+f"(d[11]), "+f"(d[12]), "+f"(d[13]), "+f"(d[14]), "+f"(d[15]), "+f"(d[16]), "+f"(d[17]), "+f"(d[18]), "+f"(d[19]), "+f"(d[20]), "+f"(d[21]), "+f"(d[22]), "+f"(d[23]), "+f"(d[24]), "+f"(d[25]), "+f"(d[26]), "+f"(d[27]), "+f"(d[28]), "+f"(d[29]), "+f"(d[30]), "+f"(d[31])
                 : "r"(a.x), "r"(a.y), "r"(a.z), "r"(a.w), "l"(db), "n"(SC));
}
template <int SC>
__device__ __forceinline__ void wgmma48(float* d, const uint4& a, uint64_t db) {
    asm volatile("wgmma.mma_async.sync.aligned.m64n48k16.f32.bf16.bf16 {%0,%1,%2,%3,%4,%5,%6,%7,%8,%9,%10,%11,%12,%13,%14,%15,%16,%17,%18,%19,%20,%21,%22,%23}, "
                 "{%24,%25,%26,%27}, %28, %29, 1, 1, 1;"
                 : "+f"(d[0]), "+f"(d[1]), "+f"(d[2]), "+f"(d[3]), "+f"(d[4]), "+f"(d[5]), "+f"(d[6]), "+f"(d[7]), "+f"(d[8]), "+f"(d[9]), "+f"(d[10]), "+f"(d[11]), "+f"(d[12]), "+f"(d[13]), "+f"(d[14]), "+f"(d[15]), "+f"(d[16]), "+f"(d[17]), "+f"(d[18]), "+f"(d[19]), "+f"(d[20]), "+f"(d[21]), "+f"(d[22]), "+f"(d[23])
                 : "r"(a.x), "r"(a.y), "r"(a.z), "r"(a.w), "l"(db), "n"(SC));
}
template <int SC>
__device__ __forceinline__ void wgmma16(float* d, const uint4& a, uint64_t db) {
    asm volatile("wgmma.mma_async.sync.aligned.m64n16k16.f32.bf16.bf16 {%0,%1,%2,%3,%4,%5,%6,%7}, "
                 "{%8,%9,%10,%11}, %12, %13, 1, 1, 1;"
                 : "+f"(d[0]), "+f"(d[1]), "+f"(d[2]), "+f"(d[3]), "+f"(d[4]), "+f"(d[5]), "+f"(d[6]), "+f"(d[7])
                 : "r"(a.x), "r"(a.y), "r"(a.z), "r"(a.w), "l"(db), "n"(SC));
}
template <int SC>
__device__ __forceinline__ void wgmma8(float* d, const uint4& a, uint64_t db) {
    asm volatile("wgmma.mma_async.sync.aligned.m64n8k16.f32.bf16.bf16 {%0,%1,%2,%3}, "
                 "{%4,%5,%6,%7}, %8, %9, 1, 1, 1;"
                 : "+f"(d[0]), "+f"(d[1]), "+f"(d[2]), "+f"(d[3])
                 : "r"(a.x), "r"(a.y), "r"(a.z), "r"(a.w), "l"(db), "n"(SC));
}
template <int SC>
__device__ __forceinline__ void wgmma64k(float* d, const uint4& a, uint64_t db) {
    asm volatile("wgmma.mma_async.sync.aligned.m64n64k16.f32.bf16.bf16 {%0,%1,%2,%3,%4,%5,%6,%7,%8,%9,%10,%11,%12,%13,%14,%15,%16,%17,%18,%19,%20,%21,%22,%23,%24,%25,%26,%27,%28,%29,%30,%31}, "
                 "{%32,%33,%34,%35}, %36, %37, 1, 1, 0;"
                 : "+f"(d[0]), "+f"(d[1]), "+f"(d[2]), "+f"(d[3]), "+f"(d[4]), "+f"(d[5]), "+f"(d[6]), "+f"(d[7]), "+f"(d[8]), "+f"(d[9]), "+f"(d[10]), "+f"(d[11]), "+f"(d[12]), "+f"(d[13]), "+f"(d[14]), "+f"(d[15]), "+f"(d[16]), "+f"(d[17]), "+f"(d[18]), "+f"(d[19]), "+f"(d[20]), "+f"(d[21]), "+f"(d[22]), "+f"(d[23]), "+f"(d[24]), "+f"(d[25]), "+f"(d[26]), "+f"(d[27]), "+f"(d[28]), "+f"(d[29]), "+f"(d[30]), "+f"(d[31])
                 : "r"(a.x), "r"(a.y), "r"(a.z), "r"(a.w), "l"(db), "n"(SC));
}

struct LnC { uint32_t rs0, nm0, rs1, nm1; };
__device__ __forceinline__ void ln_mod(uint4& a, uint4 cs, const LnC& c) {
    a.x = hfma2(hfma2(a.x, c.rs0, c.nm0), cs.x, cs.z);
    a.y = hfma2(hfma2(a.y, c.rs1, c.nm1), cs.x, cs.z);
    a.z = hfma2(hfma2(a.z, c.rs0, c.nm0), cs.y, cs.w);
    a.w = hfma2(hfma2(a.w, c.rs1, c.nm1), cs.y, cs.w);
}
__device__ __forceinline__ float rbf(float v) { return bf_lo(pack2(v, v)); }
__device__ __forceinline__ float silu_bf(float c) {
    float s = c * rcpf(1.0f + ex2f(c * -1.4426950408889634f));
    return rbf(s);
}
__device__ __forceinline__ void fma8(float* a, float s, uint4 w) {
    a[0] = fmaf(s, bf_lo(w.x), a[0]); a[1] = fmaf(s, bf_hi(w.x), a[1]);
    a[2] = fmaf(s, bf_lo(w.y), a[2]); a[3] = fmaf(s, bf_hi(w.y), a[3]);
    a[4] = fmaf(s, bf_lo(w.z), a[4]); a[5] = fmaf(s, bf_hi(w.z), a[5]);
    a[6] = fmaf(s, bf_lo(w.w), a[6]); a[7] = fmaf(s, bf_hi(w.w), a[7]);
}
__device__ __forceinline__ void red8(float* a, int lane) {
    const bool u16 = lane & 16, u8 = lane & 8, u4 = lane & 4;
#pragma unroll
    for (int k = 0; k < 4; ++k) {
        float keep = u16 ? a[k + 4] : a[k], send = u16 ? a[k] : a[k + 4];
        a[k] = keep + __shfl_xor_sync(~0u, send, 16);
    }
#pragma unroll
    for (int k = 0; k < 2; ++k) {
        float keep = u8 ? a[k + 2] : a[k], send = u8 ? a[k] : a[k + 2];
        a[k] = keep + __shfl_xor_sync(~0u, send, 8);
    }
    float keep = u4 ? a[1] : a[0], send = u4 ? a[0] : a[1];
    a[0] = keep + __shfl_xor_sync(~0u, send, 4);
    a[0] += __shfl_xor_sync(~0u, a[0], 2);
}
__device__ __forceinline__ void sumsq(uint32_t v, float& s, float& q) {
    const float a = bf_lo(v), b = bf_hi(v);
    s += a + b;
    q = fmaf(a, a, fmaf(b, b, q));
}
__device__ __forceinline__ void row_stats(float s, float q, uint32_t& rs, uint32_t& nm) {
    const float mean = s * (1.f / 512.f);
    const float var = rbf(rbf(fmaxf(fmaf(-mean, mean, q * (1.f / 512.f)), 0.f)) + 1e-5f);
    const float inv = rcpf(rbf(sqrtaf(var)));
    rs = pack2(inv, inv);
    const float m = -rbf(mean) * bf_lo(rs);
    nm = pack2(m, m);
}
__device__ __forceinline__ uint32_t one_plus(uint32_t v) { return pack2(1.0f + bf_lo(v), 1.0f + bf_hi(v)); }
__device__ __forceinline__ uint4 exp_pack(const float* s) {
    return make_uint4(pack2(ex2f(s[0]), ex2f(s[1])), pack2(ex2f(s[2]), ex2f(s[3])), pack2(ex2f(s[4]), ex2f(s[5])),
                      pack2(ex2f(s[6]), ex2f(s[7])));
}
__device__ __forceinline__ uint4 exp_pack_sum(const float* s, float& l0, float& l1) {
    const float e0 = ex2f(s[0]), e1 = ex2f(s[1]), e2 = ex2f(s[2]), e3 = ex2f(s[3]);
    const float e4 = ex2f(s[4]), e5 = ex2f(s[5]), e6 = ex2f(s[6]), e7 = ex2f(s[7]);
    l0 += (e0 + e1) + (e4 + e5);
    l1 += (e2 + e3) + (e6 + e7);
    return make_uint4(pack2(e0, e1), pack2(e2, e3), pack2(e4, e5), pack2(e6, e7));
}
template <int NB>
__device__ __forceinline__ void maxb(const float* s, float& m0, float& m1) {
#pragma unroll
    for (int i = 0; i < NB; ++i) {
        m0 = fmaxf(m0, fmaxf(fmaxf(s[8 * i], s[8 * i + 1]), fmaxf(s[8 * i + 4], s[8 * i + 5])));
        m1 = fmaxf(m1, fmaxf(fmaxf(s[8 * i + 2], s[8 * i + 3]), fmaxf(s[8 * i + 6], s[8 * i + 7])));
    }
}

__global__ void __launch_bounds__(384, 1)
fused_kernel(const __nv_bfloat16* __restrict__ x, const __nv_bfloat16* __restrict__ wqkv, const __nv_bfloat16* __restrict__ wo,
             const __nv_bfloat16* __restrict__ wg, const __nv_bfloat16* __restrict__ wu, const __nv_bfloat16* __restrict__ wd,
             const __nv_bfloat16* __restrict__ cvec, const __nv_bfloat16* __restrict__ wmod, __nv_bfloat16* __restrict__ out,
             const __grid_constant__ CUtensorMap tmX, const __grid_constant__ CUtensorMap tmQKV, const __grid_constant__ CUtensorMap tmWo,
             const __grid_constant__ CUtensorMap tmG, const __grid_constant__ CUtensorMap tmU,
             const __grid_constant__ CUtensorMap tmD) {
    extern __shared__ __align__(1024) unsigned char smem[];
    constexpr uint32_t sb = 1024;
    constexpr uint32_t bars = sb + BAR_OFF;
    asm volatile("" ::"l"(x), "l"(wmod), "l"(&g_cnt));
    const int bid = blockIdx.x;
    const int j = bid >> 3, r = bid & 7;
    const int lane = threadIdx.x & 31;
    const int warp = __shfl_sync(~0u, threadIdx.x >> 5, 0);
#define RELEASE(s0, n) mbar_arrive_lt(bars + 8 * (B_EMPTY + (s0)) + ((n) == 1 ? 0 : 8 * lane), lane, n)

    if (warp == 8) {
        if (elect()) {
#pragma unroll 1
            for (int i = 0; i < NBAR; i += 2) { mbar_init(bars + 8 * i, i < B_EMPTY ? 1 : 8); mbar_init(bars + 8 * i + 8, i < B_EMPTY ? 1 : 8); }
            fence_async_smem();
        }
        __syncwarp();
        bar_arrive(0, 288);
        bar_arrive(3, 128);
    }
    volatile unsigned* s_epoch = (volatile unsigned*)(smem + MISC_OFF);

    if (warp < 8) {
        const int w = warp, g = lane >> 2, t = lane & 3;
        const int row0 = 128 * j + 16 * w + g;
        uint4 A[32];
        LnC ln;
#define DB0(z) bdesc(sb + (z) * 16)
        uint32_t par;
        uint4* xb = g_x + (size_t)(j * 8 + w) * (X_ROWS * 32) + lane;
        asm volatile("mov.b64 %0, %0;" : "+l"(xb));
#define XROW(row) (xb + (row) * 32)
#define XR2(rt, row) (xb + (rt) * 32 + (row) * 32)
        {
            const int mrow = 256 * (bid & 1) + (threadIdx.x >> 1) * 2;
            const __nv_bfloat16* wp = wmod + (size_t)mrow * 3072 + 16 * (bid >> 1) + 8 * (lane & 1);
            const uint4 wv0 = ldg_nc(wp), wv1 = ldg_nc(wp + 3072);
            const uint32_t cv = __ldg((const uint32_t*)(cvec + mrow));
            const int srow = 128 * j + 16 * r + 2 * w + (lane >> 4);
            uint4 xs[4];
#pragma unroll
            for (int i = 0; i < 4; ++i) xs[i] = ldg_nc((const uint4*)x + (size_t)srow * 64 + i * 16 + (lane & 15));
            if (threadIdx.x == 0) *s_epoch = (ld_u32(&g_cnt) >> 7) + 1;
            float a[8];
#pragma unroll
            for (int k = 0; k < 8; ++k) a[k] = 0.f;
            fma8(a, silu_bf(bf_lo(cv)), wv0);
            fma8(a, silu_bf(bf_hi(cv)), wv1);
            red8(a, lane);
            float* red = (float*)(smem + RED_OFF);
            if ((lane & 2) == 0) red[w * 16 + (lane & 1) * 8 + (lane >> 2)] = a[0];
            float sm = 0.f, sq = 0.f;
#pragma unroll
            for (int i = 0; i < 4; ++i) { sumsq(xs[i].x, sm, sq); sumsq(xs[i].y, sm, sq); sumsq(xs[i].z, sm, sq); sumsq(xs[i].w, sm, sq); }
#pragma unroll
            for (int o = 1; o < 16; o <<= 1) { sm += __shfl_xor_sync(~0u, sm, o); sq += __shfl_xor_sync(~0u, sq, o); }
            uint32_t rs, nm;
            row_stats(sm, sq, rs, nm);
            PROF(16);
            bar_sync(0, 288);
            const unsigned epoch = *s_epoch;
            par = epoch & 1u;
            if (w == 1 && elect()) prefetch_l2((const char*)wqkv + bid * 12288, 12288);
            if ((lane & 15) == 0) st_rlx(&g_rs[srow], par, rs, nm, 0u);
            if (w == 0) {
                float4 v = *(const float4*)(red + 4 * lane);
#pragma unroll
                for (int o = 4; o < 32; o <<= 1) {
                    v.x += __shfl_xor_sync(~0u, v.x, o); v.y += __shfl_xor_sync(~0u, v.y, o);
                    v.z += __shfl_xor_sync(~0u, v.z, o); v.w += __shfl_xor_sync(~0u, v.w, o);
                }
                if (lane < 4) st_rlx(&g_m1[bid * 4 + lane], tagw(f2u(v.x), par), f2u(v.y), f2u(v.z), f2u(v.w));
                bar_sync(2, 256);
                if (lane == 0) asm volatile("red.relaxed.gpu.global.add.u32 [%0], 1;" ::"l"(&g_cnt) : "memory");
            } else {
                bar_arrive(2, 256);
            }
            PROF(0);
            asm volatile("setmaxnreg.inc.sync.aligned.u32 232;");
            {
                const uint32_t xa = sb + 3 * STAGE_BYTES + (16 * w + (lane & 15)) * 128 + (((lane >> 4) ^ lane) & 7) * 16;
#pragma unroll
                for (int i = 0; i < 8; ++i) {
                    if ((i & 3) == 0) mbar_wait(bars + 8 * (B_XF + (i >> 2)), 0);
#pragma unroll
                    for (int c = 0; c < 4; ++c) A[4 * i + c] = ldsm4((xa ^ (c * 32)) + i * STAGE_BYTES);
                }
#pragma unroll
                for (int c = 0; c < 4; ++c) xs[c] = ldsm4((xa ^ (c * 32)) + r * STAGE_BYTES);
            }
            PROF(15);
            uint4 pv[4];
            const uint4* mp = &g_m1[(threadIdx.x >> 2) * 8 + t];
#pragma unroll 1
            do {
                pv[0] = ld_rlx(mp); pv[1] = ld_rlx(mp + 4);
                pv[2] = ld_rlx(&g_rs[row0]); pv[3] = ld_rlx(&g_rs[row0 + 8]);
            } while (stale<4>(pv, par));
            mbar_arrive_lt(bars + 8 * B_GO, lane, 1);
#pragma unroll
            for (int c = 0; c < 4; ++c) st_rlx(XR2(4 * r, X_XR + c), xs[c].x, xs[c].y, xs[c].z, xs[c].w);
            const int i = threadIdx.x & 127;
            uint32_t v0 = pack2(u2f(pv[0].x) + u2f(pv[1].x), u2f(pv[0].y) + u2f(pv[1].y));
            uint32_t v1 = pack2(u2f(pv[0].z) + u2f(pv[1].z), u2f(pv[0].w) + u2f(pv[1].w));
            if (w >= 4) { v0 = one_plus(v0); v1 = one_plus(v1); }
            uint32_t* tp = (uint32_t*)(smem + TAB1_OFF) + (i >> 2) * 16 + (i & 1) * 8 + ((i >> 1) & 1) + (w >= 4 ? 0 : 2);
            tp[0] = v0; tp[4] = v1;
            ln.rs0 = pv[2].y; ln.nm0 = pv[2].z; ln.rs1 = pv[3].y; ln.nm1 = pv[3].z;
            bar_sync(1, 256);
        }
        PROF(1);

#pragma unroll 1
        for (int ph = 0; ph < 3; ++ph) {
            float acc[64];
            {
                const uint32_t tab = sb + (ph ? TAB2_OFF : TAB1_OFF) + t * 16;
                if (ph == 1) {
                    uint4 sv[2];
                    const uint4* sp = XROW(X_ST) - lane + 16 * t + g;
#pragma unroll 1
                    do {
                        sv[0] = ld_rlx(sp); sv[1] = ld_rlx(sp + 8);
#pragma unroll
                        for (int i = 0; i < NSPEC; ++i) A[i] = ld_rlx(XROW(X_X1 + i));
                    } while (stale<2>(sv, par));
#pragma unroll
                    for (int i = NSPEC; i < 32; ++i) A[i] = ld_rlx(XROW(X_X1 + i));
                    float q0 = u2f(sv[0].x) + u2f(sv[1].x), s0 = u2f(sv[0].y) + u2f(sv[1].y);
                    float q1 = u2f(sv[0].z) + u2f(sv[1].z), s1 = u2f(sv[0].w) + u2f(sv[1].w);
#pragma unroll
                    for (int o = 1; o < 4; o <<= 1) {
                        s0 += __shfl_xor_sync(~0u, s0, o); q0 += __shfl_xor_sync(~0u, q0, o);
                        s1 += __shfl_xor_sync(~0u, s1, o); q1 += __shfl_xor_sync(~0u, q1, o);
                    }
                    row_stats(s0, q0, ln.rs0, ln.nm0);
                    row_stats(s1, q1, ln.rs1, ln.nm1);
                    PROF(7);
                }
                bool bad = false;
                uint4 cs[4];
#pragma unroll
                for (int c = 0; c < 4; ++c) cs[c] = lds128(tab + c * 64);
#pragma unroll
                for (int i = 0; i < 8; ++i) {
                    const int slot = ph == 2 ? (8 + i) % NSTAGE : i, prev = ph == 2 ? (6 + i) % NSTAGE : i - 2;
                    if (i <= VCHK && ph == 1) {
                        if (i < VCHK) bad |= stale<4>(&A[4 * i], par);
                        else bad |= stale<32 - 4 * VCHK>(&A[4 * VCHK], par);
                        if (i == VCHK) {
                            bad = bar_or(bad, 4 + (w >> 2));
                            if (bad) break;
                        }
                    }
                    if (ph < 2) {
#pragma unroll
                        for (int c = 0; c < 4; ++c) ln_mod(A[4 * i + c], cs[c], ln);
                        if (i < 7) {
#pragma unroll
                            for (int c = 0; c < 4; ++c) cs[c] = lds128(tab + (4 * i + 4 + c) * 64);
                        }
                    }
                    if (w == 1) PROF2(64 + 8 * ph + i);
                    mbar_wait(bars + 8 * (B_FULL + slot), (i >= 3 && ph == 2) ? 1 : 0);
                    if (w == 1) PROF2(96 + 8 * ph + i);
                    const uint64_t d = DB0(gridDim.z - 1) + slot * 1024;
                    WG_FENCE();
#pragma unroll
                    for (int c = 0; c < 4; ++c) {
                        if (i == 0 && c == 0) wgmma128<0>(acc, A[4 * i + c], d);
                        else wgmma128<1>(acc, A[4 * i + c], d + c * 128);
                    }
                    WG_COMMIT();
                    if (w == 1) PROF2(128 + 8 * ph + i);
                    if (i > 1) {
                        WG_WAIT(2);
                        if (i < VCHK) mbar_arrive_lt(bars + 8 * (B_EMPTY + prev), lane + (ph & 1), 1);
                        else if (i > VCHK || VCHK == 2) RELEASE(prev, 1);
                        else mbar_arrive_lt(bars + 8 * (B_EMPTY + prev) - 8 * lane, lane, ph == 1 ? VCHK - 1 : 1);
                    }
                }
                WG_WAIT(0);
                pin<64>(acc);
                if (bad) { --ph; continue; }
                RELEASE(ph == 2 ? 3 : 6, 2);
            }
            if (ph) {
                uint4 hv[4];
#pragma unroll
                for (int c = 0; c < 4; ++c) { hv[c] = gate8(&acc[8 * c], &acc[32 + 8 * c]); hv[c].x = tagw(hv[c].x, par); }
#pragma unroll
                for (int c = 0; c < 4; ++c) st_rlx(XR2(r * 12 + 4 * ph, X_HH - 4 + c), hv[c].x, hv[c].y, hv[c].z, hv[c].w);
                PROF(7 + ph);
                continue;
            }
            PROF(2);
            uint4 qf;
            const uint32_t qs = sb + OUT_OFF + threadIdx.x * 16;
            {
                bar_sync(1, 256);
                pin<64>(acc);
                const uint32_t kvw = sb + KV_OFF + (16 + w) * 1024 + ((lane >> 3) & 1) * 512 + (lane >> 4) * 128 + (lane & 7) * 16;
                const uint32_t km = t ? ~0u : ~1u, kp = t ? 0u : par;
#pragma unroll
                for (int i = 0; i < 8; ++i) {
                    const uint4 v = pack8(&acc[8 * i]);
                    stsm4(kvw + (i & 3) * 24576 + (i >> 2) * 256, (v.x & km) | kp, (v.y & km) | kp, (v.z & km) | kp, (v.w & km) | kp);
                }
                if (w < 5) {
                    const uint32_t id = (2 * t == g ? 0x3f80u : 0u) | (2 * t + 1 == g ? 0x3f800000u : 0u);
                    *(uint32_t*)(smem + ONES_OFF + threadIdx.x * 4) = (w & 1) ? id : (w == 0 || (w == 4 && t == 0)) ? 0x3f803f80u : 0u;
                }
                if (__builtin_expect(j < 2, 0)) {
#pragma unroll 1
                    for (int i = 0; i < 8 * (2 - j); ++i)
                        sts128(sb + KV_OFF + (i & 3) * 24576 + (i >> 2) * 4096 + threadIdx.x * 16, 0, 0, 0, 0);
                }
                fence_async_smem();
                __syncwarp();
                mbar_arrive_lt(bars + 8 * B_KVW, lane, 1);
                PROF(17);
                float accq[32];
#pragma unroll
                for (int q = 0; q < 4; ++q) {
                    const int slot = (8 + q) % NSTAGE;
                    mbar_wait(bars + 8 * (B_FULL + slot), q == 3 ? 1 : 0);
                    const uint64_t d = DB0(blockIdx.y) + slot * 1024;
                    WG_FENCE();
#pragma unroll
                    for (int s = 0; s < 8; ++s) {
                        if (q == 0 && s == 0) wgmma64<0>(accq, A[8 * q + s], d);
                        else wgmma64<1>(accq, A[8 * q + s], d + s * 128);
                    }
                }
                WG_COMMIT();
                WG_WAIT(0);
                pin<32>(accq);
                RELEASE(lane < 3 ? 8 : -3, 4);
#pragma unroll
                for (int i = 0; i < 32; ++i) accq[i] *= 0.25f * 1.4426950408889634f;
                qf = pack8(accq);
#pragma unroll
                for (int h = 1; h < 4; ++h) {
                    const uint4 v = pack8(&accq[8 * h]);
                    sts128(qs + (h - 1) * 4096, v.x, v.y, v.z, v.w);
                }
            }
            PROF(3);
            uint4* const st_own = XROW(X_ST) - lane + r * 8 + g;

            {
                const int wg = w >> 2, w4 = w & 3;
                const int nv = 4 - 2 * j - wg;
                const int ne = nv > 0 ? 3 - w4 : 0;
                const bool pC = 2 * t <= g, pD = 2 * t + 1 <= g;
                const uint32_t mD = (pC ? 0xffffu : 0u) | (pD ? 0xffff0000u : 0u);
                const uint64_t dones = cdesc(sb + ONES_OFF, 0, 0);
                const uint32_t kb0 = sb + KV_OFF + wg * 4096;
                const uint32_t lk = kb0 + w4 * 1024 + (lane >> 4) * 512 + ((lane >> 3) & 1) * 128 + (lane & 7) * 16;
                const uint32_t lv = kb0 + w4 * 1024 + ((lane >> 3) & 1) * 512 + (lane >> 4) * 128 + (lane & 7) * 16 + 256;
                float T[4][32], E[32], m0, m1;
#define EOFF(e) ((w4 + (e) < 3 ? 1 + (e) : 13 + (e)) * 1024)
#define QK(q) wgmma64k<0>(T[q], qf, dk + 256 * (q))
#define MAXT(q) do { float a = m0, b = m1; maxb<4>(T[q], a, b); if (nv <= (q)) { m0 = a; m1 = b; } } while (0)
#define PV(q, SC) do { _Pragma("unroll") for (int i = 0; i < 4; ++i) { \
                        if (i == 0) { wgmma16<SC>(O, P[i], dv + 256 * (q)); wgmma8<SC>(L, P[i], dones); } \
                        else { wgmma16<1>(O, P[i], dv + 256 * (q) + 64 * i); wgmma8<1>(L, P[i], dones); } } } while (0)
#define EXPT(q) do { _Pragma("unroll") for (int i = 0; i < 4; ++i) P[i] = exp_pack(&T[q][8 * i]); } while (0)
#define EDGE(ko) do { \
                    float o[8], *d = &T[0][24]; \
                    mma2<0>(d, qf, ldsm4(lk + (ko) + 16384)); \
                    mma2<0>(o, qf, ldsm4(lk + (ko))); \
                    if (nv > 0) { o[0] = o[1] = o[4] = o[5] = o[6] = o[7] = -1e30f; } \
                    d[0] = pC ? d[0] : o[0]; d[1] = pD ? d[1] : o[1]; d[4] = o[4]; d[5] = o[5]; d[6] = pC ? d[6] : o[6]; d[7] = pD ? d[7] : o[7]; \
                    m0 = m1 = -3e38f; maxb<1>(d, m0, m1); \
                    _Pragma("unroll") for (int e = 0; e < 3; ++e) { \
                        mma2<0>(&T[0][8 * e], qf, ldsm4(lk + (ko) + EOFF(e))); \
                        float a = m0, b = m1; maxb<1>(&T[0][8 * e], a, b); if (e >= ne) { m0 = a; m1 = b; } \
                    } } while (0)
#define SUB(q) wgmma64k<1>(T[q], am, dones + (nv > (q) ? 0 : 32))
#define ROWMAX() do { \
                    m0 = fmaxf(m0, __shfl_xor_sync(~0u, m0, 1)); m1 = fmaxf(m1, __shfl_xor_sync(~0u, m1, 1)); \
                    m0 = fmaxf(m0, __shfl_xor_sync(~0u, m0, 2)); m1 = fmaxf(m1, __shfl_xor_sync(~0u, m1, 2)); \
                    const float h0 = rbf(-m0), h1 = rbf(-m1); \
                    const uint32_t n0 = pack2(h0, -m0 - h0), n1 = pack2(h1, -m1 - h1); \
                    m0 = h0 + bf_hi(n0); m1 = h1 + bf_hi(n1); \
                    am = make_uint4(t == 0 ? n0 : 0xf100u, t == 0 ? n1 : 0xf100u, 0u, 0u); \
                    WG_FENCE(); SUB(1); WG_COMMIT(); } while (0)
#define SHIFTE() do { _Pragma("unroll") for (int e = 0; e < 4; ++e) { \
                        const float b0 = e < ne ? -1e30f : m0, b1 = e < ne ? -1e30f : m1; \
                        _Pragma("unroll") for (int i = 0; i < 8; ++i) E[8 * e + i] = T[0][8 * e + i] + ((i & 2) ? b1 : b0); } } while (0)
                uint4 am;
                st_rlx(XR2(4 * r, X_O + 3), par ^ 1u, 0, 0, 0);
                if (t == 0) st_rlx(st_own, par ^ 1u, 0, 0, 0);
                mbar_wait(bars + 8 * B_HALO, 0);
                PROF(18);
                {
                    const uint64_t dk = cdesc(kb0, 128, 512);
                    WG_FENCE();
                    QK(1); QK(2); QK(3);
                    WG_COMMIT();
                }
                EDGE(0);
                WG_WAIT(0);
                pin<32>(T[1]); pin<32>(T[2]); pin<32>(T[3]);
                MAXT(1); MAXT(2); MAXT(3);
                ROWMAX();
                WG_WAIT(0);
                pin<32>(T[1]);
                bar_sync_if(wg, 2, 256);
#pragma unroll 1
                for (int h = 0;; ++h) {
                    const uint32_t hn = (h < 3 ? h + 1 : 3) * 24576;
                    const uint64_t dv = cdesc(kb0 + h * 24576 + 256, 512, 128);
                    const uint64_t dk = cdesc(kb0 + hn, 128, 512);
                    qf = lds128(qs + h * 4096);
                    const uint32_t zero = *(volatile uint32_t*)(smem + ONES_OFF + 256);
                    float O[8], L[4], O2[8], L2[4], l0 = 0.f, l1 = 0.f;
                    mbar_wait(bars + 8 * (B_HALO + ((h + 1) & 3)), 0);
                    WG_FENCE();
                    SUB(2);
                    WG_COMMIT();
                    SHIFTE();
                    {
                        uint4 P[4];
                        EDGE(hn);
                        EXPT(1);
                        P[3].w |= (f2u(m0) | f2u(m1)) & zero;
                        WG_FENCE();
                        QK(1);
                        SUB(3);
                        PV(1, 0);
                        WG_COMMIT();
                    }
                    WG_WAIT(1);
                    pin<32>(T[2]);
                    {
                        uint4 P[4];
                        EXPT(2);
                        WG_FENCE();
                        QK(2);
                        PV(2, 1);
                        WG_COMMIT();
                    }
                    WG_WAIT(1);
                    pin<32>(T[1]); pin<32>(T[3]);
                    bar_arrive_if(h + wg == 0, 2, 256);
                    {
                        uint4 P[4];
                        MAXT(1);
                        EXPT(3);
                        P[3].w |= (f2u(m0) | f2u(m1)) & zero;
                        WG_FENCE();
                        QK(3);
                        WG_COMMIT();
                        PV(3, 1);
                        WG_COMMIT();
                    }
                    WG_WAIT(2);
                    pin<32>(T[2]);
                    MAXT(2);
                    const uint4 ones = make_uint4(0x3f803f80u, 0x3f803f80u, 0u, 0u);
                    E[0] = u2f(f2u(E[0]) | (f2u(T[2][0]) & zero));
#pragma unroll
                    for (int e = 0; e < 4; ++e) {
                        if (e == 1) {
                            WG_WAIT(1);
                            pin<32>(T[3]);
                            MAXT(3);
                        }
                        if (e == 3) ROWMAX();
                        const uint4 P = exp_pack(&E[8 * e]);
                        if (e == 0) { mma2<0>(O2, P, ldsm4t(lv + h * 24576 + EOFF(e))); mma2<0, 1>(L2, P, ones); }
                        else {
                            mma2<1, 1>(L2, P, ones);
                            if (e < 3) mma2<1>(O2, P, ldsm4t(lv + h * 24576 + EOFF(e)));
                            else {
                                mma2<1>(O2, make_uint4(P.x & ~mD, 0u, P.z, P.w & ~mD), ldsm4t(lv + h * 24576));
                                mma2<1>(O2, make_uint4(P.x & mD, P.y, 0u, P.w & mD), ldsm4t(lv + h * 24576 + 16384));
                            }
                        }
                    }
                    WG_WAIT(0);
                    pin<32>(T[1]); pin<8>(O);
                    pin<4>(L);
                    const float i0 = rcpf(L[0] + L2[0]), i1 = rcpf(L[2] + L2[2]);
                    st_rlx(XR2(4 * r + h, X_O), tagw(pack2((O[0] + O2[0]) * i0, (O[1] + O2[1]) * i0), par),
                           pack2((O[2] + O2[2]) * i1, (O[3] + O2[3]) * i1), pack2((O[4] + O2[4]) * i0, (O[5] + O2[5]) * i0),
                           pack2((O[6] + O2[6]) * i1, (O[7] + O2[7]) * i1));
                    if (4 * r < NSPEC) st_rlx(XR2(4 * r + h, X_X1), par ^ 1u, 0, 0, 0);
                    if (h == 3) break;
                    PROF(19 + h);
                    RELEASE(1 + h + (h >> 1), 1 + (h & 1));
                }
            }
            PROF(4);

            {
                uint4 xr[4];
#pragma unroll
                for (int c = 0; c < 4; ++c) xr[c] = ld_rlx(XR2(4 * r, X_XR + c));
                float acc[32];
#pragma unroll
                for (int m = 0; m < 4; ++m) mbar_wait(bars + 8 * (B_FULL + 7 + m), 1);
                const uint64_t d0 = DB0(blockIdx.z) + 7 * 1024;
#pragma unroll
                for (int h = 0; h < 4; ++h) {
                    if (h == 0) poll<24>(A, XROW(X_O), [](int i) { return 128 * (i & 7) + 32 * (i >> 3); }, par);
                    if (h == 3) poll<8>(&A[24], XROW(X_O + 3), [](int i) { return 128 * i; }, par);
                    if (h == 0 || h == 3) WG_FENCE();
#pragma unroll
                    for (int i = 0; i < 8; ++i) {
                        if (h == 0 && i == 0) wgmma64<0>(acc, A[8 * h + i], d0);
                        else wgmma64<1>(acc, A[8 * h + i], d0 + i * 512 + h * 128);
                    }
                }
                WG_COMMIT();
                RELEASE(5, 2);
                mbar_wait(bars + 8 * B_TAB2, 0);
                WG_WAIT(0);
                pin<32>(acc);
                RELEASE(7, 4);
                PROF(5);
                float s0 = 0.f, s1 = 0.f, q0 = 0.f, q1 = 0.f;
                uint32_t xo[16];
#pragma unroll
                for (int b = 0; b < 8; ++b) {
                    const float2 ga = *(const float2*)(smem + GA_OFF + (8 * b + 2 * t) * 4);
                    const uint32_t u0 = (b & 1) ? xr[b >> 1].z : xr[b >> 1].x, u1 = (b & 1) ? xr[b >> 1].w : xr[b >> 1].y;
                    const float v0 = fmaf(ga.x, acc[4 * b], bf_lo(u0)), v1 = fmaf(ga.y, acc[4 * b + 1], bf_hi(u0));
                    const float v2 = fmaf(ga.x, acc[4 * b + 2], bf_lo(u1)), v3 = fmaf(ga.y, acc[4 * b + 3], bf_hi(u1));
                    xo[2 * b] = pack2(v0, v1);
                    xo[2 * b + 1] = pack2(v2, v3);
                    s0 += v0 + v1; q0 = fmaf(v0, v0, fmaf(v1, v1, q0));
                    s1 += v2 + v3; q1 = fmaf(v2, v2, fmaf(v3, v3, q1));
                }
                sts128(qs, xo[0], xo[4], xo[8], xo[12]);
#pragma unroll
                for (int i = 0; i < 4; ++i) xo[4 * i] = tagw(xo[4 * i], par);
#pragma unroll
                for (int i = 0; i < 4; ++i) st_rlx(XR2(4 * r, X_X1 + i), xo[4 * i], xo[4 * i + 1], xo[4 * i + 2], xo[4 * i + 3]);
#pragma unroll
                for (int o = 1; o < 4; o <<= 1) {
                    s0 += __shfl_xor_sync(~0u, s0, o); q0 += __shfl_xor_sync(~0u, q0, o);
                    s1 += __shfl_xor_sync(~0u, s1, o); q1 += __shfl_xor_sync(~0u, q1, o);
                }
                if (t == 0) st_rlx(st_own, tagw(f2u(q0), par), f2u(s0), f2u(q1), f2u(s1));
            }
            PROF(6);
            ln.rs0 = ln.nm0 = ln.rs1 = ln.nm1 = 0;
        }
        const uint4* const hp = XR2((r & 6) * 12, X_HH);
        auto off8 = [](int k) { return ((k >> 2) * 12 + (k & 3)) * 32; };
        {
            float ag[24], au[24];
#pragma unroll
            for (int i = 0; i < 8; ++i) {
                const int n = 38 + i;
                mbar_wait(bars + 8 * (B_FULL + n % NSTAGE), (n / NSTAGE) & 1);
                const uint64_t d = DB0(gridDim.y - 1) + (n % NSTAGE) * 1024;
                WG_FENCE();
#pragma unroll
                for (int c = 0; c < 4; ++c) {
                    if (i == 0 && c == 0) {
                        wgmma48<0>(ag, A[4 * i + c], d);
                        wgmma48<0>(au, A[4 * i + c], d + 512);
                    } else {
                        wgmma48<1>(ag, A[4 * i + c], d + c * 128);
                        wgmma48<1>(au, A[4 * i + c], d + 512 + c * 128);
                    }
                }
                WG_COMMIT();
                if (i < 3) st_rlx(XR2(r * 12, X_HH + 8 + i), par ^ 1u, 0, 0, 0);
                else if (i < 7) st_rlx(XR2(((r + 6) & 7) * 12, X_PT + 5 + i), par ^ 1u, 0, 0, 0);
                if (i > 0) {
                    WG_WAIT(1);
                    RELEASE((n - 1) % NSTAGE, 1);
                }
                if (i == 2 || i == 4) {
#pragma unroll
                    for (int c = 0; c < 8; ++c) A[4 * i - 8 + c] = ld_rlx(hp + 64 * (i - 2) + off8(c));
                }
            }
            WG_WAIT(0);
            pin<24>(ag); pin<24>(au);
            RELEASE(45 % NSTAGE, 1);
#pragma unroll
            for (int c = 0; c < 3; ++c) A[16 + c] = gate8(&ag[8 * c], &au[8 * c]);
        }
        PROF(10);
        {
            float acc[32];
            uint4 P[4], Q[12], X1[4];
            int slot = 46 % NSTAGE, fpar = 0;
            uint4* dst = xb;
#pragma unroll
            for (int c = 0; c < 3; ++c) {
                A[16 + c].x = tagw(A[16 + c].x, par);
                st_rlx(XR2(r * 12, X_HH + 8 + c), A[16 + c].x, A[16 + c].y, A[16 + c].z, A[16 + c].w);
            }
            P[0] = P[1] = P[2] = P[3] = make_uint4(0, 0, 0, 0);
            validate<16>(A, hp, [](int k) { return (((k >> 2) & 1) * 12 + (k & 3) + (k >> 3) * 4) * 32; }, par);
#pragma unroll 1
            for (int cb = 0; cb < 4; ++cb) {
                uint64_t d;
#pragma unroll
                for (int p = 0; p < 3; ++p) {
                    mbar_wait(bars + 8 * (B_FULL + slot), fpar);
                    d = DB0(blockDim.y - 1) + slot * 1024;
                    if (++slot == NSTAGE) { slot = 0; fpar = 1; }
                    WG_FENCE();
#pragma unroll
                    for (int k = 0; k < (p < 2 ? 8 : 3); ++k) {
                        if (p == 0 && k == 0) wgmma64<0>(acc, A[k], d);
                        else if (p < 2) wgmma64<1>(acc, A[8 * p + k], d + k * 128);
                        else wgmma64<1>(acc, A[16 + k], d + (r & 1) * 512 + k * 128);
                    }
                    if (p == 0 && cb > 0) {
#pragma unroll
                        for (int c = 0; c < 4; ++c) st_rlx(dst + c * 32, P[c].x, P[c].y, P[c].z, P[c].w);
                    }
                }
                if (cb == 0) poll<3>(&A[19], XR2((r ^ 1) * 12, X_HH + 8), [](int c) { return 32 * c; }, par);
                WG_FENCE();
#pragma unroll
                for (int k = 0; k < 3; ++k) wgmma64<1>(acc, A[19 + k], d + (~r & 1) * 512 + k * 128);
                WG_COMMIT();
                if (cb == 3) {
#pragma unroll
                    for (int i = 0; i < 4; ++i) X1[i] = ld_rlx(XR2(4 * r, X_X1 + i));
#pragma unroll
                    for (int i = 0; i < 8; ++i) Q[i] = ld_rlx(XR2(r * 12, X_PT + i));
                }
                WG_WAIT(0);
                pin<32>(acc);
                if (cb == 3) break;
                mbar_arrive_lt(bars + 8 * (B_EMPTY + 46 % NSTAGE), lane + cb, 1);
                dst = XR2(((r + 2 + 2 * cb) & 7) * 12 + 4 * cb, X_PT);
#pragma unroll
                for (int c = 0; c < 4; ++c) { P[c] = pack8(&acc[8 * c]); P[c].x = tagw(P[c].x, par); }
            }
            const uint64_t did = cdesc(sb + ONES_OFF + 128, 128, 128);
            {
                const uint4 e = lds128(sb + OUT_OFF + threadIdx.x * 16);
                X1[0].x = e.x; X1[1].x = e.y; X1[2].x = e.z; X1[3].x = e.w;
            }
            PROF(11);
            validate<8>(Q, XR2(r * 12, X_PT), [](int i) { return 32 * i; }, par);
            poll<4>(Q + 8, XR2(r * 12, X_PT + 8), [](int i) { return 32 * i; }, par);
            float ap[4][8];
            WG_FENCE();
#pragma unroll
            for (int i = 0; i < 12; ++i) {
                if (i < 4) wgmma16<0>(ap[i], Q[i], did);
                else wgmma16<1>(ap[i & 3], Q[i], did);
            }
            WG_COMMIT();
            WG_WAIT(0);
            pin<32>(&ap[0][0]);
            PROF(13);
            const uint32_t stg = sb + OUT_OFF + 4096 + w * 1024;
            uint32_t ln2;
            asm volatile("mov.u32 %0, %%laneid;" : "=r"(ln2));
            char* const op = (char*)out + (size_t)(128 * j + 16 * w) * 1024 + 128 * r + (ln2 >> 2) * 1024 + (ln2 & 3) * 16;
            const int wr = (lane & 7) + (lane & 8), rr = lane >> 2;
#pragma unroll
            for (int hf = 0; hf < 2; ++hf) {
#pragma unroll
                for (int i = 2 * hf; i < 2 * hf + 2; ++i) {
                    const uint32_t xw[4] = {X1[i].x, X1[i].y, X1[i].z, X1[i].w};
                    uint32_t o[4];
#pragma unroll
                    for (int e = 0; e < 4; ++e) {
                        const float2 gb = *(const float2*)(smem + GB_OFF + (16 * i + 8 * (e >> 1) + 2 * t) * 4);
                        o[e] = pack2(fmaf(gb.x, acc[8 * i + 2 * e] + ap[i][2 * e], bf_lo(xw[e])),
                                     fmaf(gb.y, acc[8 * i + 2 * e + 1] + ap[i][2 * e + 1], bf_hi(xw[e])));
                    }
                    stsm4(stg + wr * 64 + (((2 * (i & 1) + (lane >> 4)) ^ (wr >> 1)) & 3) * 16, o[0], o[1], o[2], o[3]);
                }
                __syncwarp();
#pragma unroll
                for (int k = 0; k < 2; ++k) {
                    const uint4 v = lds128(stg + (rr + 8 * k) * 64 + ((t ^ (rr >> 1)) & 3) * 16);
                    *(uint4*)(op + k * 8192 + 64 * hf) = v;
                }
                __syncwarp();
            }
            mbar_arrive_lt(bars + 8 * B_DONE, lane, 1);
        }
        PROF(12);
        PROF_DUMP();
    } else {
        asm volatile("setmaxnreg.dec.sync.aligned.u32 40;");
        if (warp == 8) {
            if (elect()) {
                if (s2u(smem) != sb) DIE();
                int pos = 0, ph = 1;
                uint32_t fb, dst;
                auto next = [&]() {
                    mbar_wait_b(bars + 8 * (B_EMPTY + pos), ph);
                    fb = bars + 8 * (B_FULL + pos);
                    dst = sb + pos * STAGE_BYTES;
                    mbar_expect(fb, STAGE_BYTES);
                    if (++pos == NSTAGE) { pos = 0; ph ^= 1; }
                };
#pragma unroll 1
                for (int n = 0; n < 8; ++n) {
                    if ((n & 3) == 0) mbar_expect(bars + 8 * (B_XF + (n >> 2)), 4 * STAGE_BYTES);
                    tma2d(sb + (3 + n) * STAGE_BYTES, &tmX, 64 * n, 128 * j, bars + 8 * (B_XF + (n >> 2)));
                }
#pragma unroll 1
                for (int n = 0; n < 12; ++n) {
                    if (n == 3) mbar_wait_b(bars + 8 * B_GO, 0);
                    next();
                    PROF2(n);
                    tma2d(dst, &tmQKV, (n < 8 ? 512 : 0) + 64 * r, n < 8 ? 64 * n : 128 * n - 1024, fb);
                    tma2d(dst + 8192, &tmQKV, (n < 8 ? 1024 : 0) + 64 * r, n < 8 ? 64 * n : 128 * n - 960, fb);
                }
                PROF(0);
#pragma unroll 1
                for (pos = 1; pos < 7; ++pos) {
                    mbar_wait_b(bars + 8 * (B_EMPTY + pos), 0);
                    mbar_arrive(bars + 8 * (B_FULL + pos));
                }
                mbar_wait_b(bars + 8 * (B_HALO + 3), 0);
                int c = 64 * r, r0 = 0, dr = 64, step = 128;
                const CUtensorMap *m0 = &tmWo, *m1 = &tmWo;
#pragma unroll 1
                for (int s = 0; s < 8; ++s) {
                    const int cnt = s == 0 ? 4 : s < 4 ? 8 : 3;
#pragma unroll 1
                    for (int n = 0; n < cnt; ++n) {
                        if (pos == 2) mbar_wait_b(bars + 8 * B_PUB, 0);
                        next();
                        tma2d(dst, m0, c, r0, fb);
                        tma2d(dst + 8192, m1, c, r0 + dr, fb);
                        r0 += step;
                    }
                    PROF(1 + s);
                    step = 64;
                    if (s < 3) { m0 = &tmG; m1 = &tmU; c = 176 * r + 64 * s; r0 = 0; dr = 0; }
                    else { m0 = m1 = &tmD; c = 64 * ((r + 2 * s - 4) & 7); r0 = 176 * (r & 6); dr = 176; }
                }
                mbar_wait_b(bars + 8 * B_DONE, 0);
            }
            PROF_DUMP();
        } else {
            bar_sync(3, 128);
            mbar_wait(bars + 8 * B_GO, 0);
            const unsigned epoch = *s_epoch;
            if (warp < 11) {
                const int nn = j < 2 ? j : 2;
                const unsigned* fl = (const unsigned*)(g_kv + (size_t)(bid - 8 * (lane + 1)) * 2048 + 511);
                unsigned fv = epoch, fv2 = epoch;
                if (lane < nn) { fv = ld_u32(fl + (10 - warp) * 2048); fv2 = ld_u32(fl + (12 - warp) * 2048); }
                mbar_wait(bars + 8 * B_KVW, 0);
                if (warp == 9 && elect()) {
                    if (j < 15) {
#pragma unroll 1
                        for (int h = 0; h < 4; ++h) {
                            bulk_s2g(g_kv + (size_t)bid * 2048 + h * 512, sb + KV_OFF + h * 24576 + 16384, 8192);
                            if (h < 2) __nanosleep(PUBGAP);
                        }
                        asm volatile("cp.async.bulk.commit_group;" ::: "memory");
                    }
                }
                PROF(1);
                uint32_t lph = 0;
#pragma unroll 1
                for (int h = 10 - warp; h < 4;) {
#pragma unroll 1
                    while ((fv ^ epoch) & 1u) fv = ld_u32(fl + h * 2048);
                    __syncwarp();
                    if (h < 2) { if (lph == 0) PROF(8); else PROF(10); }
                    if (elect()) {
                        mbar_expect(bars + 8 * (B_HLD + h), nn * 8192);
#pragma unroll 1
                        for (int n = 1; n <= nn; ++n)
                            bulk_g2s(sb + KV_OFF + h * 24576 + (2 - n) * 8192, g_kv + (size_t)(bid - 8 * n) * 2048 + h * 512, 8192,
                                     bars + 8 * (B_HLD + h));
                    }
                    mbar_wait(bars + 8 * (B_HLD + h), lph);
                    if (h < 2 && lph == 0) PROF(9);
                    uint32_t bad = 0;
#pragma unroll 16
                    for (int i = 0; i < 16 * nn; ++i)
                        bad |= *(volatile uint32_t*)(smem + KV_OFF + h * 24576 + 16384 - 512 - i * 512 + lane * 16) ^ epoch;
                    if (__any_sync(~0u, bad & 1u)) { lph ^= 1; continue; }
                    mbar_arrive_lt(bars + 8 * (B_HALO + h), lane, 1);
                    PROF(3 + h);
                    lph = 0;
                    h += 2;
                    fv = fv2;
                }
                if (warp == 9) {
                    asm volatile("cp.async.bulk.wait_group.read 0;" ::: "memory");
                    __syncwarp();
                    mbar_arrive_lt(bars + 8 * B_PUB, lane, 1);
                }
                PROF(2);
                PROF_DUMP();
            }
        }
    }
    if (warp == 11) {
        const unsigned epoch = *s_epoch;
                const uint32_t par = epoch & 1u;
                if (lane < 8) {
                    const char* p = lane < 4 ? (const char*)(wmod + (size_t)(4 * bid + lane) * 3072 + 1024)
                                  : lane == 4 ? (const char*)wo + bid * 4096
                                  : (const char*)(lane == 5 ? wg : lane == 6 ? wu : wd) + bid * 11008;
                    prefetch_l2(p, lane < 5 ? 4096 : 11008);
                }
                mbar_wait(bars + 8 * (B_FULL + 10), 0);
                {
                    const int half = lane & 1, rg = lane >> 1;
                    float a[8];
#pragma unroll
                    for (int k = 0; k < 8; ++k) a[k] = 0.f;
#pragma unroll 1
                    for (int b = 0; b < 8; ++b) {
                        const int row = b * 64 + rg * 4;
                        uint4 wv[4];
#pragma unroll
                        for (int i = 0; i < 4; ++i) wv[i] = ldg_nc(wmod + (size_t)(row + i) * 3072 + 1024 + 16 * bid + 8 * half);
                        const uint2 cv = *(const uint2*)(cvec + row);
                        fma8(a, silu_bf(bf_lo(cv.x)), wv[0]); fma8(a, silu_bf(bf_hi(cv.x)), wv[1]);
                        fma8(a, silu_bf(bf_lo(cv.y)), wv[2]); fma8(a, silu_bf(bf_hi(cv.y)), wv[3]);
                    }
                    red8(a, lane);
                    float* red2 = (float*)(smem + RED_OFF + 512);
                    if ((lane & 2) == 0) red2[half * 8 + (lane >> 2)] = a[0];
                    __syncwarp();
                    if (lane < 4) {
                        const uint4 v = *(const uint4*)(red2 + 4 * lane);
                        st_rlx(&g_m2[4 * bid + lane], tagw(v.x, par), v.y, v.z, v.w);
                    }
                }
                PROF(1);
                mbar_wait(bars + 8 * (B_HALO + 1), 0);
                uint32_t* tab2 = (uint32_t*)(smem + TAB2_OFF);
#pragma unroll 1
                for (int q = 0; q < 9; ++q) {
                    const int e = q < 8 ? 128 + q * 32 + lane : (lane < 16 ? 16 * r + lane : 368 + 16 * r + lane);
                    uint4 v;
                    poll<1>(&v, &g_m2[e], [](int) { return 0; }, par);
                    uint32_t v0 = pack2(u2f(v.x), u2f(v.y)), v1 = pack2(u2f(v.z), u2f(v.w));
                    if (q < 8) {
                        const int ep = (q & 3) * 64 + lane * 2;
                        const int isc = q >> 2;
                        if (isc) { v0 = one_plus(v0); v1 = one_plus(v1); }
                        const int kap = ep >> 3, wi = ep & 7;
                        const int o0 = (kap * 4 + (wi & 3)) * 4 + (wi >> 2) + (isc ? 0 : 2);
                        tab2[o0] = v0;
                        tab2[o0 + 4] = v1;
                    } else {
                        *(float4*)(smem + GA_OFF + lane * 16) = make_float4(bf_lo(v0), bf_hi(v0), bf_lo(v1), bf_hi(v1));
                    }
                }
                __syncwarp();
                if (lane == 0) mbar_arrive(bars + 8 * B_TAB2);
                PROF(2);
                PROF_DUMP();
    }
}

typedef CUresult (*EncodeFn)(CUtensorMap*, CUtensorMapDataType, cuuint32_t, void*, const cuuint64_t*, const cuuint64_t*,
                             const cuuint32_t*, const cuuint32_t*, CUtensorMapInterleave, CUtensorMapSwizzle,
                             CUtensorMapL2promotion, CUtensorMapFloatOOBfill);

void make2d(EncodeFn enc, CUtensorMap* m, const void* p, uint64_t cols, uint64_t rows, uint32_t box_rows = 64) {
    cuuint64_t dims[2] = {cols, rows};
    cuuint64_t str[1] = {cols * 2};
    cuuint32_t box[2] = {64, box_rows}, es[2] = {1, 1};
    enc(m, CU_TENSOR_MAP_DATA_TYPE_BFLOAT16, 2, (void*)p, dims, str, box, es, CU_TENSOR_MAP_INTERLEAVE_NONE,
        CU_TENSOR_MAP_SWIZZLE_128B, CU_TENSOR_MAP_L2_PROMOTION_L2_128B, CU_TENSOR_MAP_FLOAT_OOB_FILL_NONE);
}

}

extern "C" void kernel_launch(void* const* d_in, const int* in_sizes, int n_in, void* d_out, int out_size) {
    const __nv_bfloat16* x = (const __nv_bfloat16*)d_in[0];
    const __nv_bfloat16* wqkv = (const __nv_bfloat16*)d_in[1];
    const __nv_bfloat16* wo = (const __nv_bfloat16*)d_in[2];
    const __nv_bfloat16* wg = (const __nv_bfloat16*)d_in[4];
    const __nv_bfloat16* wu = (const __nv_bfloat16*)d_in[5];
    const __nv_bfloat16* wd = (const __nv_bfloat16*)d_in[6];
    const __nv_bfloat16* c = (const __nv_bfloat16*)d_in[7];
    const __nv_bfloat16* wmod = (const __nv_bfloat16*)d_in[8];

    void* fn = nullptr;
    cudaDriverEntryPointQueryResult qr;
    cudaGetDriverEntryPoint("cuTensorMapEncodeTiled", &fn, cudaEnableDefault, &qr);
    EncodeFn enc = (EncodeFn)fn;
    CUtensorMap tmX, tmQKV, tmWo, tmG, tmU, tmD;
    make2d(enc, &tmX, x, 512, 2048, 128);
    make2d(enc, &tmQKV, wqkv, 1536, 512);
    make2d(enc, &tmWo, wo, 512, 512);
    make2d(enc, &tmG, wg, 1376, 512);
    make2d(enc, &tmU, wu, 1376, 512);
    make2d(enc, &tmD, wd, 512, 1376);
    cudaFuncSetAttribute(fused_kernel, cudaFuncAttributeMaxDynamicSharedMemorySize, SMEM_BYTES + PROF_EXTRA);
    fused_kernel<<<128, 384, SMEM_BYTES + PROF_EXTRA, cudaStreamPerThread>>>(x, wqkv, wo, wg, wu, wd, c, wmod, (__nv_bfloat16*)d_out, tmX, tmQKV, tmWo,
                                                               tmG, tmU, tmD);
}
```

```cpp
#include <cuda_runtime.h>
#include <cuda_bf16.h>
#include <cuda.h>
#include <stdint.h>

namespace {

constexpr int NSTAGE = 11;
constexpr int STAGE_BYTES = 16384;
constexpr int KV_OFF = 1 * STAGE_BYTES;
constexpr int OUT_OFF = NSTAGE * STAGE_BYTES;
constexpr int TAB1_OFF = OUT_OFF + 12288;
constexpr int TAB2_OFF = TAB1_OFF + 2048;
constexpr int GA_OFF = TAB2_OFF + 2048;
constexpr int GB_OFF = GA_OFF + 256;
constexpr int ONES_OFF = GB_OFF + 256;
constexpr int RED_OFF = TAB2_OFF;
constexpr int SCHED_OFF = ONES_OFF + 512;
constexpr int MISC_OFF = SCHED_OFF + 58 * 16;
constexpr int BAR_OFF = MISC_OFF + 16;
constexpr int B_FULL = 0, B_HALO = 11, B_TAB2 = 15, B_PUB = 16, B_HLD = 18;
constexpr int B_EMPTY = 22, B_KVW = 33, B_GO = 34, B_DONE = 35, B_XF = 36, NBAR = 38;
constexpr int SMEM_BYTES = BAR_OFF + NBAR * 8;

#define NB1 12
#define UNITS0 0x2210
#define UNITS1 0x776354
#define SLP0 0
#define GATE 1
#define SKEW 1
#define PUBGAP 250
constexpr int SPIN_LIMIT = 1 << 21;
#define DIE() asm volatile("st.global.u32 [%0], %1;" ::"l"(0ull), "r"(0) : "memory")

__device__ const uint4 c_sched[64] = {
    {512u | 0u << 16, 64u | 0u << 8 | 4095u << 16, 512u | 0u << 16, 0u | 1u << 4 | 1u << 5 | (0) << 8 | 1u << 16 | 1u << 24},
    {512u | 64u << 16, 64u | 0u << 8 | 4095u << 16, 512u | 0u << 16, 1u | 1u << 4 | 1u << 5 | (0) << 8 | 1u << 16 | 1u << 24},
    {512u | 128u << 16, 64u | 0u << 8 | 4095u << 16, 512u | 0u << 16, 2u | 1u << 4 | 1u << 5 | (0) << 8 | 1u << 16 | 1u << 24},
    {512u | 192u << 16, 64u | 0u << 8 | 4095u << 16, 512u | 0u << 16, 3u | 1u << 4 | 1u << 5 | (B_GO) << 8 | 1u << 16 | 1u << 24},
    {512u | 256u << 16, 64u | 0u << 8 | 4095u << 16, 512u | 0u << 16, 4u | 1u << 4 | 1u << 5 | (0) << 8 | 1u << 16 | 1u << 24},
    {512u | 320u << 16, 64u | 0u << 8 | 4095u << 16, 512u | 0u << 16, 5u | 1u << 4 | 1u << 5 | (0) << 8 | 1u << 16 | 1u << 24},
    {512u | 384u << 16, 64u | 0u << 8 | 4095u << 16, 512u | 0u << 16, 6u | 1u << 4 | 1u << 5 | (0) << 8 | 1u << 16 | 1u << 24},
    {512u | 448u << 16, 64u | 0u << 8 | 4095u << 16, 512u | 0u << 16, 7u | 1u << 4 | 1u << 5 | (0) << 8 | 1u << 16 | 1u << 24},
    {0u | 0u << 16, 64u | 0u << 8 | 4095u << 16, 0u | 64u << 16, 8u | 1u << 4 | 1u << 5 | (0) << 8 | 1u << 16 | 1u << 24},
    {0u | 128u << 16, 64u | 0u << 8 | 4095u << 16, 0u | 64u << 16, 9u | 1u << 4 | 1u << 5 | (0) << 8 | 1u << 16 | 1u << 24},
    {0u | 256u << 16, 64u | 0u << 8 | 4095u << 16, 0u | 64u << 16, 10u | 1u << 4 | 1u << 5 | (0) << 8 | 1u << 16 | 1u << 24},
    {0u | 384u << 16, 64u | 0u << 8 | 4095u << 16, 0u | 64u << 16, 0u | 1u << 4 | 0u << 5 | (0) << 8 | 1u << 16 | 1u << 24},
    {0u | 0u << 16, 0u | 0u << 8 | 4095u << 16, 0u | 0u << 16, 1u | 0u << 4 | 0u << 5 | (0) << 8 | 0u << 16 | 0u << 24},
    {0u | 0u << 16, 0u | 0u << 8 | 4095u << 16, 0u | 0u << 16, 2u | 0u << 4 | 0u << 5 | (0) << 8 | 0u << 16 | 0u << 24},
    {0u | 0u << 16, 0u | 0u << 8 | 4095u << 16, 0u | 0u << 16, 3u | 0u << 4 | 0u << 5 | (0) << 8 | 0u << 16 | 0u << 24},
    {0u | 0u << 16, 0u | 0u << 8 | 4095u << 16, 0u | 0u << 16, 4u | 0u << 4 | 0u << 5 | (0) << 8 | 0u << 16 | 0u << 24},
    {0u | 0u << 16, 0u | 0u << 8 | 4095u << 16, 0u | 0u << 16, 5u | 0u << 4 | 0u << 5 | (0) << 8 | 0u << 16 | 0u << 24},
    {0u | 0u << 16, 0u | 0u << 8 | 4095u << 16, 0u | 0u << 16, 6u | 0u << 4 | 0u << 5 | (0) << 8 | 0u << 16 | 0u << 24},
    {0u | 0u << 16, 64u | 0u << 8 | 4095u << 16, 0u | 64u << 16, 7u | 1u << 4 | 0u << 5 | (B_PUB) << 8 | 2u << 16 | 2u << 24},
    {0u | 128u << 16, 64u | 0u << 8 | 4095u << 16, 0u | 64u << 16, 8u | 1u << 4 | 0u << 5 | (0) << 8 | 2u << 16 | 2u << 24},
    {0u | 256u << 16, 64u | 0u << 8 | 4095u << 16, 0u | 64u << 16, 9u | 1u << 4 | 0u << 5 | (B_PUB) << 8 | 2u << 16 | 2u << 24},
    {0u | 384u << 16, 64u | 0u << 8 | 4095u << 16, 0u | 64u << 16, 10u | 1u << 4 | 0u << 5 | (0) << 8 | 2u << 16 | 2u << 24},
    {0u | 0u << 16, 176u | 0u << 8 | 4095u << 16, 0u | 0u << 16, 0u | 1u << 4 | 1u << 5 | (0) << 8 | 3u << 16 | 4u << 24},
    {0u | 64u << 16, 176u | 0u << 8 | 4095u << 16, 0u | 0u << 16, 1u | 1u << 4 | 1u << 5 | (0) << 8 | 3u << 16 | 4u << 24},
    {0u | 128u << 16, 176u | 0u << 8 | 4095u << 16, 0u | 0u << 16, 2u | 1u << 4 | 1u << 5 | (0) << 8 | 3u << 16 | 4u << 24},
    {0u | 192u << 16, 176u | 0u << 8 | 4095u << 16, 0u | 0u << 16, 3u | 1u << 4 | 1u << 5 | (0) << 8 | 3u << 16 | 4u << 24},
    {0u | 256u << 16, 176u | 0u << 8 | 4095u << 16, 0u | 0u << 16, 4u | 1u << 4 | 1u << 5 | (0) << 8 | 3u << 16 | 4u << 24},
    {0u | 320u << 16, 176u | 0u << 8 | 4095u << 16, 0u | 0u << 16, 5u | 1u << 4 | 1u << 5 | (0) << 8 | 3u << 16 | 4u << 24},
    {0u | 384u << 16, 176u | 0u << 8 | 4095u << 16, 0u | 0u << 16, 6u | 1u << 4 | 1u << 5 | (0) << 8 | 3u << 16 | 4u << 24},
    {0u | 448u << 16, 176u | 0u << 8 | 4095u << 16, 0u | 0u << 16, 7u | 1u << 4 | 1u << 5 | (0) << 8 | 3u << 16 | 4u << 24},
    {64u | 0u << 16, 176u | 0u << 8 | 4095u << 16, 0u | 0u << 16, 8u | 1u << 4 | 1u << 5 | (0) << 8 | 3u << 16 | 4u << 24},
    {64u | 64u << 16, 176u | 0u << 8 | 4095u << 16, 0u | 0u << 16, 9u | 1u << 4 | 1u << 5 | (0) << 8 | 3u << 16 | 4u << 24},
    {64u | 128u << 16, 176u | 0u << 8 | 4095u << 16, 0u | 0u << 16, 10u | 1u << 4 | 1u << 5 | (0) << 8 | 3u << 16 | 4u << 24},
    {64u | 192u << 16, 176u | 0u << 8 | 4095u << 16, 0u | 0u << 16, 0u | 1u << 4 | 0u << 5 | (0) << 8 | 3u << 16 | 4u << 24},
    {64u | 256u << 16, 176u | 0u << 8 | 4095u << 16, 0u | 0u << 16, 1u | 1u << 4 | 0u << 5 | (0) << 8 | 3u << 16 | 4u << 24},
    {64u | 320u << 16, 176u | 0u << 8 | 4095u << 16, 0u | 0u << 16, 2u | 1u << 4 | 0u << 5 | (0) << 8 | 3u << 16 | 4u << 24},
    {64u | 384u << 16, 176u | 0u << 8 | 4095u << 16, 0u | 0u << 16, 3u | 1u << 4 | 0u << 5 | (0) << 8 | 3u << 16 | 4u << 24},
    {64u | 448u << 16, 176u | 0u << 8 | 4095u << 16, 0u | 0u << 16, 4u | 1u << 4 | 0u << 5 | (0) << 8 | 3u << 16 | 4u << 24},
    {128u | 0u << 16, 176u | 0u << 8 | 4095u << 16, 0u | 0u << 16, 5u | 1u << 4 | 0u << 5 | (0) << 8 | 3u << 16 | 4u << 24},
    {128u | 64u << 16, 176u | 0u << 8 | 4095u << 16, 0u | 0u << 16, 6u | 1u << 4 | 0u << 5 | (0) << 8 | 3u << 16 | 4u << 24},
    {128u | 128u << 16, 176u | 0u << 8 | 4095u << 16, 0u | 0u << 16, 7u | 1u << 4 | 0u << 5 | (0) << 8 | 3u << 16 | 4u << 24},
    {128u | 192u << 16, 176u | 0u << 8 | 4095u << 16, 0u | 0u << 16, 8u | 1u << 4 | 0u << 5 | (0) << 8 | 3u << 16 | 4u << 24},
    {128u | 256u << 16, 176u | 0u << 8 | 4095u << 16, 0u | 0u << 16, 9u | 1u << 4 | 0u << 5 | (0) << 8 | 3u << 16 | 4u << 24},
    {128u | 320u << 16, 176u | 0u << 8 | 4095u << 16, 0u | 0u << 16, 10u | 1u << 4 | 0u << 5 | (0) << 8 | 3u << 16 | 4u << 24},
    {128u | 384u << 16, 176u | 0u << 8 | 4095u << 16, 0u | 0u << 16, 0u | 1u << 4 | 1u << 5 | (0) << 8 | 3u << 16 | 4u << 24},
    {128u | 448u << 16, 176u | 0u << 8 | 4095u << 16, 0u | 0u << 16, 1u | 1u << 4 | 1u << 5 | (0) << 8 | 3u << 16 | 4u << 24},
    {128u | 0u << 16, 64u | 176u << 8 | 511u << 16, 0u | 176u << 16, 2u | 1u << 4 | 1u << 5 | (0) << 8 | 5u << 16 | 5u << 24},
    {128u | 64u << 16, 64u | 176u << 8 | 511u << 16, 0u | 176u << 16, 3u | 1u << 4 | 1u << 5 | (0) << 8 | 5u << 16 | 5u << 24},
    {128u | 128u << 16, 64u | 176u << 8 | 511u << 16, 0u | 176u << 16, 4u | 1u << 4 | 1u << 5 | (0) << 8 | 5u << 16 | 5u << 24},
    {256u | 0u << 16, 64u | 176u << 8 | 511u << 16, 0u | 176u << 16, 5u | 1u << 4 | 1u << 5 | (0) << 8 | 5u << 16 | 5u << 24},
    {256u | 64u << 16, 64u | 176u << 8 | 511u << 16, 0u | 176u << 16, 6u | 1u << 4 | 1u << 5 | (0) << 8 | 5u << 16 | 5u << 24},
    {256u | 128u << 16, 64u | 176u << 8 | 511u << 16, 0u | 176u << 16, 7u | 1u << 4 | 1u << 5 | (0) << 8 | 5u << 16 | 5u << 24},
    {384u | 0u << 16, 64u | 176u << 8 | 511u << 16, 0u | 176u << 16, 8u | 1u << 4 | 1u << 5 | (0) << 8 | 5u << 16 | 5u << 24},
    {384u | 64u << 16, 64u | 176u << 8 | 511u << 16, 0u | 176u << 16, 9u | 1u << 4 | 1u << 5 | (0) << 8 | 5u << 16 | 5u << 24},
    {384u | 128u << 16, 64u | 176u << 8 | 511u << 16, 0u | 176u << 16, 10u | 1u << 4 | 1u << 5 | (0) << 8 | 5u << 16 | 5u << 24},
    {512u | 0u << 16, 64u | 176u << 8 | 511u << 16, 0u | 176u << 16, 0u | 1u << 4 | 0u << 5 | (0) << 8 | 5u << 16 | 5u << 24},
    {512u | 64u << 16, 64u | 176u << 8 | 511u << 16, 0u | 176u << 16, 1u | 1u << 4 | 0u << 5 | (0) << 8 | 5u << 16 | 5u << 24},
    {512u | 128u << 16, 64u | 176u << 8 | 511u << 16, 0u | 176u << 16, 2u | 1u << 4 | 0u << 5 | (0) << 8 | 5u << 16 | 5u << 24},
};

__device__ uint4 g_kv[16 * 8 * 2048];
constexpr int X_O = 0, X_X1 = 32, X_HH = 64, X_PT = 160, X_XR = 256, X_ST = 288, X_ROWS = 290;
__device__ uint4 g_x[16 * 8 * X_ROWS * 32];
__device__ uint4 g_m1[512];
__device__ uint4 g_m2[512];
__device__ uint4 g_rs[2048];
__device__ unsigned g_cnt;
#define PROF(i) do {} while (0)
#define PROF_DUMP() do {} while (0)
#define PROF_EXTRA 0
#define PROF2(i) do {} while (0)

__device__ __forceinline__ uint32_t s2u(const void* p) { return (uint32_t)__cvta_generic_to_shared(p); }
__device__ __forceinline__ bool elect() {
    uint32_t p;
    asm volatile("{\n.reg .pred p;\nelect.sync _|p, 0xffffffff;\nselp.u32 %0, 1, 0, p;\n}" : "=r"(p));
    return p;
}
__device__ __forceinline__ void mbar_init(uint32_t b, int c) {
    asm volatile("mbarrier.init.shared::cta.b64 [%0], %1;" ::"r"(b), "r"(c) : "memory");
}
__device__ __forceinline__ void mbar_expect(uint32_t b, uint32_t bytes) {
    asm volatile("mbarrier.arrive.expect_tx.shared::cta.b64 _, [%0], %1;" ::"r"(b), "r"(bytes) : "memory");
}
__device__ __forceinline__ void mbar_arrive(uint32_t b) {
    asm volatile("mbarrier.arrive.shared::cta.b64 _, [%0];" ::"r"(b) : "memory");
}
__device__ __forceinline__ void mbar_arrive1(uint32_t b) {
    asm volatile("{\n.reg .pred p;\nelect.sync _|p, 0xffffffff;\n@p mbarrier.arrive.shared::cta.b64 _, [%0];\n}" ::"r"(b) : "memory");
}
__device__ __forceinline__ void mbar_arrive_lt(uint32_t b, int a, int n) {
    asm volatile("{\n.reg .pred p;\nsetp.lt.s32 p, %1, %2;\n@p mbarrier.arrive.shared::cta.b64 _, [%0];\n}" ::"r"(b), "r"(a), "r"(n) : "memory");
}
__device__ __forceinline__ void mbar_wait(uint32_t b, uint32_t ph) {
    asm volatile("{\n.reg .pred p;\nLOOP_%=:\nmbarrier.try_wait.parity.shared::cta.b64 p, [%0], %1;\n@!p bra LOOP_%=;\n}"
                 ::"r"(b), "r"(ph) : "memory");
}
__device__ __forceinline__ void mbar_wait_b(uint32_t b, uint32_t ph) {
    asm volatile(
        "{\n.reg .pred p;\n.reg .u32 n;\n"
        "mov.u32 n, 0;\n"
        "LOOP_%=:\n"
        "mbarrier.try_wait.parity.shared::cta.b64 p, [%0], %1;\n"
        "@p bra DONE_%=;\n"
        "add.u32 n, n, 1;\n"
        "setp.lt.u32 p, n, %2;\n"
        "@p bra LOOP_%=;\n"
        "st.global.u32 [%3], n;\n"
        "DONE_%=:\n}" ::"r"(b), "r"(ph), "n"(SPIN_LIMIT), "l"(0ull) : "memory");
}
__device__ __forceinline__ void bar_sync(int id, int n) { asm volatile("bar.sync %0, %1;" ::"r"(id), "r"(n) : "memory"); }
__device__ __forceinline__ void bar_arrive(int id, int n) { asm volatile("bar.arrive %0, %1;" ::"r"(id), "r"(n) : "memory"); }
__device__ __forceinline__ void bar_sync_if(int c, int id, int n) {
    asm volatile("{\n.reg .pred p;\nsetp.ne.u32 p, %0, 0;\n@p bar.sync %1, %2;\n}" ::"r"(c), "r"(id), "r"(n) : "memory");
}
__device__ __forceinline__ void bar_arrive_if(int c, int id, int n) {
    asm volatile("{\n.reg .pred p;\nsetp.ne.u32 p, %0, 0;\n@p bar.arrive %1, %2;\n}" ::"r"(c), "r"(id), "r"(n) : "memory");
}
__device__ __forceinline__ void fence_async_smem() { asm volatile("fence.proxy.async.shared::cta;" ::: "memory"); }

__device__ __forceinline__ void tma2d(uint32_t dst, const CUtensorMap* m, int c0, int c1, uint32_t bar) {
    asm volatile("cp.async.bulk.tensor.2d.shared::cluster.global.mbarrier::complete_tx::bytes [%0], [%1, {%3, %4}], [%2];"
                 ::"r"(dst), "l"(m), "r"(bar), "r"(c0), "r"(c1) : "memory");
}
__device__ __forceinline__ void bulk_g2s(uint32_t dst, const void* src, uint32_t bytes, uint32_t bar) {
    asm volatile("cp.async.bulk.shared::cluster.global.mbarrier::complete_tx::bytes [%0], [%1], %2, [%3];"
                 ::"r"(dst), "l"(src), "r"(bytes), "r"(bar) : "memory");
}
__device__ __forceinline__ void bulk_s2g(void* dst, uint32_t src, uint32_t bytes) {
    asm volatile("cp.async.bulk.global.shared::cta.bulk_group [%0], [%1], %2;" ::"l"(dst), "r"(src), "r"(bytes) : "memory");
}
__device__ __forceinline__ void prefetch_l2(const void* p, uint32_t bytes) {
    asm volatile("cp.async.bulk.prefetch.L2.global [%0], %1;" ::"l"(p), "r"(bytes) : "memory");
}
__device__ __forceinline__ uint4 ldg_nc(const void* p) {
    uint4 v;
    asm volatile("ld.global.nc.v4.u32 {%0,%1,%2,%3}, [%4];" : "=r"(v.x), "=r"(v.y), "=r"(v.z), "=r"(v.w) : "l"(p));
    return v;
}
__device__ __forceinline__ unsigned ld_u32(const unsigned* p) {
    unsigned v;
    asm volatile("ld.relaxed.gpu.global.u32 %0, [%1];" : "=r"(v) : "l"(p) : "memory");
    return v;
}
__device__ __forceinline__ uint4 ld_rlx(const void* p) {
    uint4 v;
    asm volatile("ld.relaxed.gpu.global.v4.u32 {%0,%1,%2,%3}, [%4];" : "=r"(v.x), "=r"(v.y), "=r"(v.z), "=r"(v.w) : "l"(p) : "memory");
    return v;
}
__device__ __forceinline__ void st_rlx(void* p, uint32_t x, uint32_t y, uint32_t z, uint32_t w) {
    asm volatile("st.relaxed.gpu.global.v4.u32 [%0], {%1,%2,%3,%4};" ::"l"(p), "r"(x), "r"(y), "r"(z), "r"(w) : "memory");
}
__device__ __forceinline__ uint32_t tagw(uint32_t x, uint32_t par) {
    uint32_t d;
    asm("lop3.b32 %0, %1, 0xfffffffe, %2, 0xea;" : "=r"(d) : "r"(x), "r"(par));
    return d;
}
template <int N>
__device__ __forceinline__ bool stale(const uint4* v, uint32_t par) {
    uint32_t bad = 0;
#pragma unroll
    for (int i = 0; i < N; ++i) asm("lop3.b32 %0, %1, %2, %0, 0xbe;" : "+r"(bad) : "r"(v[i].x), "r"(par));
    return __any_sync(~0u, bad & 1u);
}
template <int N, class F>
__device__ __forceinline__ void poll(uint4* v, const uint4* p, F off, uint32_t par) {
#pragma unroll 1
    do {
#pragma unroll
        for (int i = 0; i < N; ++i) v[i] = ld_rlx(p + off(i));
    } while (stale<N>(v, par));
}
template <int N, class F>
__device__ __forceinline__ void validate(uint4* v, const uint4* p, F off, uint32_t par) {
    if (__builtin_expect(stale<N>(v, par), 0)) poll<N>(v, p, off, par);
}
__device__ __forceinline__ uint4 lds128(uint32_t a) {
    uint4 v;
    asm volatile("ld.shared.v4.u32 {%0,%1,%2,%3}, [%4];" : "=r"(v.x), "=r"(v.y), "=r"(v.z), "=r"(v.w) : "r"(a) : "memory");
    return v;
}
__device__ __forceinline__ uint32_t lds32(uint32_t a) {
    uint32_t v;
    asm volatile("ld.shared.u32 %0, [%1];" : "=r"(v) : "r"(a) : "memory");
    return v;
}
__device__ __forceinline__ void sts128(uint32_t a, uint32_t x, uint32_t y, uint32_t z, uint32_t w) {
    asm volatile("st.shared.v4.u32 [%0], {%1,%2,%3,%4};" ::"r"(a), "r"(x), "r"(y), "r"(z), "r"(w) : "memory");
}
__device__ __forceinline__ void stsm4(uint32_t a, uint32_t x, uint32_t y, uint32_t z, uint32_t w) {
    asm volatile("stmatrix.sync.aligned.m8n8.x4.shared.b16 [%0], {%1,%2,%3,%4};" ::"r"(a), "r"(x), "r"(y), "r"(z), "r"(w) : "memory");
}
__device__ __forceinline__ uint4 ldsm4(uint32_t a) {
    uint4 v;
    asm volatile("ldmatrix.sync.aligned.m8n8.x4.shared.b16 {%0,%1,%2,%3}, [%4];" : "=r"(v.x), "=r"(v.y), "=r"(v.z), "=r"(v.w) : "r"(a) : "memory");
    return v;
}
__device__ __forceinline__ uint4 ldsm4t(uint32_t a) {
    uint4 v;
    asm volatile("ldmatrix.sync.aligned.m8n8.x4.trans.shared.b16 {%0,%1,%2,%3}, [%4];" : "=r"(v.x), "=r"(v.y), "=r"(v.z), "=r"(v.w) : "r"(a) : "memory");
    return v;
}
template <int ACC, int NT = 2>
__device__ __forceinline__ void mma2(float* d, const uint4& a, const uint4& b) {
#pragma unroll
    for (int i = 0; i < NT; ++i)
        asm("mma.sync.aligned.m16n8k16.row.col.f32.bf16.bf16.f32 {%0,%1,%2,%3}, {%4,%5,%6,%7}, {%8,%9}, {%10,%11,%12,%13};"
            : "=f"(d[4 * i]), "=f"(d[4 * i + 1]), "=f"(d[4 * i + 2]), "=f"(d[4 * i + 3])
            : "r"(a.x), "r"(a.y), "r"(a.z), "r"(a.w), "r"(i ? b.z : b.x), "r"(i ? b.w : b.y), "f"(ACC ? d[4 * i] : 0.f),
              "f"(ACC ? d[4 * i + 1] : 0.f), "f"(ACC ? d[4 * i + 2] : 0.f), "f"(ACC ? d[4 * i + 3] : 0.f));
}
__device__ __forceinline__ uint32_t pack2(float lo, float hi) {
    uint32_t d;
    asm("cvt.rn.bf16x2.f32 %0, %1, %2;" : "=r"(d) : "f"(hi), "f"(lo));
    return d;
}
__device__ __forceinline__ uint4 pack8(const float* a) {
    return make_uint4(pack2(a[0], a[1]), pack2(a[2], a[3]), pack2(a[4], a[5]), pack2(a[6], a[7]));
}
__device__ __forceinline__ float bf_lo(uint32_t x) { return __uint_as_float(x << 16); }
__device__ __forceinline__ float bf_hi(uint32_t x) { return __uint_as_float(x & 0xffff0000u); }
__device__ __forceinline__ float u2f(uint32_t v) { return __uint_as_float(v); }
__device__ __forceinline__ uint32_t f2u(float v) { return __float_as_uint(v); }
__device__ __forceinline__ uint32_t hfma2(uint32_t a, uint32_t b, uint32_t c) {
    uint32_t d;
    asm("fma.rn.bf16x2 %0, %1, %2, %3;" : "=r"(d) : "r"(a), "r"(b), "r"(c));
    return d;
}
__device__ __forceinline__ uint32_t hmul2(uint32_t a, uint32_t b) {
    uint32_t d;
    asm("mul.rn.bf16x2 %0, %1, %2;" : "=r"(d) : "r"(a), "r"(b));
    return d;
}
__device__ __forceinline__ uint4 gate8(const float* a, const float* b) {
    const uint4 u = pack8(a), v = pack8(b);
    return make_uint4(hmul2(u.x, v.x), hmul2(u.y, v.y), hmul2(u.z, v.z), hmul2(u.w, v.w));
}
__device__ __forceinline__ float ex2f(float x) {
    float y;
    asm("ex2.approx.ftz.f32 %0, %1;" : "=f"(y) : "f"(x));
    return y;
}
__device__ __forceinline__ float rcpf(float x) {
    float y;
    asm("rcp.approx.ftz.f32 %0, %1;" : "=f"(y) : "f"(x));
    return y;
}
__device__ __forceinline__ float sqrtaf(float x) {
    float y;
    asm("sqrt.approx.ftz.f32 %0, %1;" : "=f"(y) : "f"(x));
    return y;
}
#define WG_FENCE() asm volatile("wgmma.fence.sync.aligned;" ::: "memory")
#define WG_COMMIT() asm volatile("wgmma.commit_group.sync.aligned;" ::: "memory")
#define WG_WAIT(n) asm volatile("wgmma.wait_group.sync.aligned %0;" ::"n"(n) : "memory")
template <int N>
__device__ __forceinline__ void pin(float* d) {
#pragma unroll
    for (int i = 0; i < N; ++i) asm volatile("" : "+f"(d[i])::"memory");
}

__device__ __forceinline__ uint64_t bdesc(uint32_t addr) {
    return (uint64_t)((addr >> 4) | (512u << 16)) | ((uint64_t)(64u | (1u << 30)) << 32);
}
__device__ __forceinline__ uint64_t cdesc(uint32_t addr, uint32_t lbo, uint32_t sbo) {
    return (uint64_t)((addr >> 4) | ((lbo >> 4) << 16)) | ((uint64_t)(sbo >> 4) << 32);
}
template <int SC>
__device__ __forceinline__ void wgmma128(float* d, const uint4& a, uint64_t db) {
    asm volatile("wgmma.mma_async.sync.aligned.m64n128k16.f32.bf16.bf16 {%0,%1,%2,%3,%4,%5,%6,%7,%8,%9,%10,%11,%12,%13,%14,%15,%16,%17,%18,%19,%20,%21,%22,%23,%24,%25,%26,%27,%28,%29,%30,%31,%32,%33,%34,%35,%36,%37,%38,%39,%40,%41,%42,%43,%44,%45,%46,%47,%48,%49,%50,%51,%52,%53,%54,%55,%56,%57,%58,%59,%60,%61,%62,%63}, "
                 "{%64,%65,%66,%67}, %68, %69, 1, 1, 1;"
                 : "+f"(d[0]), "+f"(d[1]), "+f"(d[2]), "+f"(d[3]), "+f"(d[4]), "+f"(d[5]), "+f"(d[6]), "+f"(d[7]), "+f"(d[8]), "+f"(d[9]), "+f"(d[10]), "+f"(d[11]), "+f"(d[12]), "+f"(d[13]), "+f"(d[14]), "+f"(d[15]), "+f"(d[16]), "+f"(d[17]), "+f"(d[18]), "+f"(d[19]), "+f"(d[20]), "+f"(d[21]), "+f"(d[22]), "+f"(d[23]), "+f"(d[24]), "+f"(d[25]), "+f"(d[26]), "+f"(d[27]), "+f"(d[28]), "+f"(d[29]), "+f"(d[30]), "+f"(d[31]), "+f"(d[32]), "+f"(d[33]), "+f"(d[34]), "+f"(d[35]), "+f"(d[36]), "+f"(d[37]), "+f"(d[38]), "+f"(d[39]), "+f"(d[40]), "+f"(d[41]), "+f"(d[42]), "+f"(d[43]), "+f"(d[44]), "+f"(d[45]), "+f"(d[46]), "+f"(d[47]), "+f"(d[48]), "+f"(d[49]), "+f"(d[50]), "+f"(d[51]), "+f"(d[52]), "+f"(d[53]), "+f"(d[54]), "+f"(d[55]), "+f"(d[56]), "+f"(d[57]), "+f"(d[58]), "+f"(d[59]), "+f"(d[60]), "+f"(d[61]), "+f"(d[62]), "+f"(d[63])
                 : "r"(a.x), "r"(a.y), "r"(a.z), "r"(a.w), "l"(db), "n"(SC));
}
template <int SC>
__device__ __forceinline__ void wgmma64(float* d, const uint4& a, uint64_t db) {
    asm volatile("wgmma.mma_async.sync.aligned.m64n64k16.f32.bf16.bf16 {%0,%1,%2,%3,%4,%5,%6,%7,%8,%9,%10,%11,%12,%13,%14,%15,%16,%17,%18,%19,%20,%21,%22,%23,%24,%25,%26,%27,%28,%29,%30,%31}, "
                 "{%32,%33,%34,%35}, %36, %37, 1, 1, 1;"
                 : "+f"(d[0]), "+f"(d[1]), "+f"(d[2]), "+f"(d[3]), "+f"(d[4]), "+f"(d[5]), "+f"(d[6]), "+f"(d[7]), "+f"(d[8]), "+f"(d[9]), "+f"(d[10]), "+f"(d[11]), "+f"(d[12]), "+f"(d[13]), "+f"(d[14]), "+f"(d[15]), "+f"(d[16]), "+f"(d[17]), "+f"(d[18]), "+f"(d[19]), "+f"(d[20]), "+f"(d[21]), "+f"(d[22]), "+f"(d[23]), "+f"(d[24]), "+f"(d[25]), "+f"(d[26]), "+f"(d[27]), "+f"(d[28]), "+f"(d[29]), "+f"(d[30]), "+f"(d[31])
                 : "r"(a.x), "r"(a.y), "r"(a.z), "r"(a.w), "l"(db), "n"(SC));
}
template <int SC>
__device__ __forceinline__ void wgmma48(float* d, const uint4& a, uint64_t db) {
    asm volatile("wgmma.mma_async.sync.aligned.m64n48k16.f32.bf16.bf16 {%0,%1,%2,%3,%4,%5,%6,%7,%8,%9,%10,%11,%12,%13,%14,%15,%16,%17,%18,%19,%20,%21,%22,%23}, "
                 "{%24,%25,%26,%27}, %28, %29, 1, 1, 1;"
                 : "+f"(d[0]), "+f"(d[1]), "+f"(d[2]), "+f"(d[3]), "+f"(d[4]), "+f"(d[5]), "+f"(d[6]), "+f"(d[7]), "+f"(d[8]), "+f"(d[9]), "+f"(d[10]), "+f"(d[11]), "+f"(d[12]), "+f"(d[13]), "+f"(d[14]), "+f"(d[15]), "+f"(d[16]), "+f"(d[17]), "+f"(d[18]), "+f"(d[19]), "+f"(d[20]), "+f"(d[21]), "+f"(d[22]), "+f"(d[23])
                 : "r"(a.x), "r"(a.y), "r"(a.z), "r"(a.w), "l"(db), "n"(SC));
}
template <int SC>
__device__ __forceinline__ void wgmma16(float* d, const uint4& a, uint64_t db) {
    asm volatile("wgmma.mma_async.sync.aligned.m64n16k16.f32.bf16.bf16 {%0,%1,%2,%3,%4,%5,%6,%7}, "
                 "{%8,%9,%10,%11}, %12, %13, 1, 1, 1;"
                 : "+f"(d[0]), "+f"(d[1]), "+f"(d[2]), "+f"(d[3]), "+f"(d[4]), "+f"(d[5]), "+f"(d[6]), "+f"(d[7])
                 : "r"(a.x), "r"(a.y), "r"(a.z), "r"(a.w), "l"(db), "n"(SC));
}
template <int SC>
__device__ __forceinline__ void wgmma8(float* d, const uint4& a, uint64_t db) {
    asm volatile("wgmma.mma_async.sync.aligned.m64n8k16.f32.bf16.bf16 {%0,%1,%2,%3}, "
                 "{%4,%5,%6,%7}, %8, %9, 1, 1, 1;"
                 : "+f"(d[0]), "+f"(d[1]), "+f"(d[2]), "+f"(d[3])
                 : "r"(a.x), "r"(a.y), "r"(a.z), "r"(a.w), "l"(db), "n"(SC));
}
template <int SC>
__device__ __forceinline__ void wgmma64k(float* d, const uint4& a, uint64_t db) {
    asm volatile("wgmma.mma_async.sync.aligned.m64n64k16.f32.bf16.bf16 {%0,%1,%2,%3,%4,%5,%6,%7,%8,%9,%10,%11,%12,%13,%14,%15,%16,%17,%18,%19,%20,%21,%22,%23,%24,%25,%26,%27,%28,%29,%30,%31}, "
                 "{%32,%33,%34,%35}, %36, %37, 1, 1, 0;"
                 : "+f"(d[0]), "+f"(d[1]), "+f"(d[2]), "+f"(d[3]), "+f"(d[4]), "+f"(d[5]), "+f"(d[6]), "+f"(d[7]), "+f"(d[8]), "+f"(d[9]), "+f"(d[10]), "+f"(d[11]), "+f"(d[12]), "+f"(d[13]), "+f"(d[14]), "+f"(d[15]), "+f"(d[16]), "+f"(d[17]), "+f"(d[18]), "+f"(d[19]), "+f"(d[20]), "+f"(d[21]), "+f"(d[22]), "+f"(d[23]), "+f"(d[24]), "+f"(d[25]), "+f"(d[26]), "+f"(d[27]), "+f"(d[28]), "+f"(d[29]), "+f"(d[30]), "+f"(d[31])
                 : "r"(a.x), "r"(a.y), "r"(a.z), "r"(a.w), "l"(db), "n"(SC));
}

struct LnC { uint32_t rs0, nm0, rs1, nm1; };
__device__ __forceinline__ void ln_mod(uint4& a, uint4 cs, const LnC& c) {
    a.x = hfma2(hfma2(a.x, c.rs0, c.nm0), cs.x, cs.z);
    a.y = hfma2(hfma2(a.y, c.rs1, c.nm1), cs.x, cs.z);
    a.z = hfma2(hfma2(a.z, c.rs0, c.nm0), cs.y, cs.w);
    a.w = hfma2(hfma2(a.w, c.rs1, c.nm1), cs.y, cs.w);
}
__device__ __forceinline__ float rbf(float v) { return bf_lo(pack2(v, v)); }
__device__ __forceinline__ float silu_bf(float c) {
    float s = c * rcpf(1.0f + ex2f(c * -1.4426950408889634f));
    return rbf(s);
}
__device__ __forceinline__ void fma8(float* a, float s, uint4 w) {
    a[0] = fmaf(s, bf_lo(w.x), a[0]); a[1] = fmaf(s, bf_hi(w.x), a[1]);
    a[2] = fmaf(s, bf_lo(w.y), a[2]); a[3] = fmaf(s, bf_hi(w.y), a[3]);
    a[4] = fmaf(s, bf_lo(w.z), a[4]); a[5] = fmaf(s, bf_hi(w.z), a[5]);
    a[6] = fmaf(s, bf_lo(w.w), a[6]); a[7] = fmaf(s, bf_hi(w.w), a[7]);
}
__device__ __forceinline__ void red8(float* a, int lane) {
    const bool u16 = lane & 16, u8 = lane & 8, u4 = lane & 4;
#pragma unroll
    for (int k = 0; k < 4; ++k) {
        float keep = u16 ? a[k + 4] : a[k], send = u16 ? a[k] : a[k + 4];
        a[k] = keep + __shfl_xor_sync(~0u, send, 16);
    }
#pragma unroll
    for (int k = 0; k < 2; ++k) {
        float keep = u8 ? a[k + 2] : a[k], send = u8 ? a[k] : a[k + 2];
        a[k] = keep + __shfl_xor_sync(~0u, send, 8);
    }
    float keep = u4 ? a[1] : a[0], send = u4 ? a[0] : a[1];
    a[0] = keep + __shfl_xor_sync(~0u, send, 4);
    a[0] += __shfl_xor_sync(~0u, a[0], 2);
}
__device__ __forceinline__ void sumsq(uint32_t v, float& s, float& q) {
    const float a = bf_lo(v), b = bf_hi(v);
    s += a + b;
    q = fmaf(a, a, fmaf(b, b, q));
}
__device__ __forceinline__ void row_stats(float s, float q, uint32_t& rs, uint32_t& nm) {
    const float mean = s * (1.f / 512.f);
    const float var = rbf(rbf(fmaxf(fmaf(-mean, mean, q * (1.f / 512.f)), 0.f)) + 1e-5f);
    const float inv = rcpf(rbf(sqrtaf(var)));
    rs = pack2(inv, inv);
    const float m = -rbf(mean) * bf_lo(rs);
    nm = pack2(m, m);
}
__device__ __forceinline__ uint32_t one_plus(uint32_t v) { return pack2(1.0f + bf_lo(v), 1.0f + bf_hi(v)); }
__device__ __forceinline__ uint4 exp_pack(const float* s) {
    return make_uint4(pack2(ex2f(s[0]), ex2f(s[1])), pack2(ex2f(s[2]), ex2f(s[3])), pack2(ex2f(s[4]), ex2f(s[5])),
                      pack2(ex2f(s[6]), ex2f(s[7])));
}
template <int NB>
__device__ __forceinline__ void maxb(const float* s, float& m0, float& m1) {
#pragma unroll
    for (int i = 0; i < NB; ++i) {
        m0 = fmaxf(m0, fmaxf(fmaxf(s[8 * i], s[8 * i + 1]), fmaxf(s[8 * i + 4], s[8 * i + 5])));
        m1 = fmaxf(m1, fmaxf(fmaxf(s[8 * i + 2], s[8 * i + 3]), fmaxf(s[8 * i + 6], s[8 * i + 7])));
    }
}

struct Maps { CUtensorMap m[6]; };

__global__ void __launch_bounds__(384, 1)
fused_kernel(const __nv_bfloat16* __restrict__ x, const __nv_bfloat16* __restrict__ wqkv, const __nv_bfloat16* __restrict__ wo,
             const __nv_bfloat16* __restrict__ wg, const __nv_bfloat16* __restrict__ wu, const __nv_bfloat16* __restrict__ wd,
             const __nv_bfloat16* __restrict__ cvec, const __nv_bfloat16* __restrict__ wmod, __nv_bfloat16* __restrict__ out,
             const __grid_constant__ Maps tm) {
    extern __shared__ __align__(1024) unsigned char smem[];
    constexpr uint32_t sb = 1024;
    constexpr uint32_t bars = sb + BAR_OFF;
    const int bid = blockIdx.x;
    const int j = bid >> 3, r = bid & 7;
    const int lane = threadIdx.x & 31;
    const int warp = __shfl_sync(~0u, threadIdx.x >> 5, 0);
#define RELEASE(s0, n) do { _Pragma("unroll") for (int q_ = 0; q_ < (n); ++q_) mbar_arrive1(bars + 8 * (B_EMPTY + (s0) + q_)); } while (0)

    if (warp == 8) {
        if (elect()) {
            mbar_init(bars + 8 * B_XF, 1);
            mbar_init(bars + 8 * B_XF + 8, 1);
            mbar_expect(bars + 8 * B_XF, 4 * STAGE_BYTES);
            mbar_expect(bars + 8 * B_XF + 8, 4 * STAGE_BYTES);
#pragma unroll 1
            for (int n = 0; n < 8; ++n) tma2d(sb + (3 + n) * STAGE_BYTES, &tm.m[0], 64 * n, 128 * j, bars + 8 * (B_XF + (n >> 2)));
            PROF(1);
            if (s2u(smem) != sb) DIE();
#pragma unroll 1
            for (int i = 0; i < B_XF; i += 2) { mbar_init(bars + 8 * i, i < B_EMPTY ? 1 : 8); mbar_init(bars + 8 * i + 8, i < B_EMPTY ? 1 : 8); }
        }
        __syncwarp();
        bar_arrive(0, 288);
    }
    volatile unsigned* s_epoch = (volatile unsigned*)(smem + MISC_OFF);

    if (warp < 8) {
        const int w = warp, g = lane >> 2, t = lane & 3;
        const int row0 = 128 * j + 16 * w + g;
        uint4 A[32];
        LnC ln;
#define DB0(z) bdesc(sb + (z) * 16)
        uint32_t par;
        uint4* xb = g_x + (size_t)(j * 8 + w) * (X_ROWS * 32) + lane;
        asm volatile("mov.b64 %0, %0;" : "+l"(xb));
#define XROW(row) (xb + (row) * 32)
#define XR2(rt, row) (xb + (rt) * 32 + (row) * 32)
        {
            const unsigned epoch = (ld_u32(&g_cnt) >> 7) + 1;
            const int mrow = 256 * (bid & 1) + (threadIdx.x >> 1) * 2;
            const __nv_bfloat16* wp = wmod + (size_t)mrow * 3072 + 16 * (bid >> 1) + 8 * (lane & 1);
            const uint4 wv0 = ldg_nc(wp), wv1 = ldg_nc(wp + 3072);
            const uint32_t cv = __ldg((const uint32_t*)(cvec + mrow));
            const int srow = 128 * j + 16 * r + 2 * w + (lane >> 4);
            uint4 xs[4];
#pragma unroll
            for (int i = 0; i < 4; ++i) xs[i] = ldg_nc((const uint4*)x + (size_t)srow * 64 + i * 16 + (lane & 15));
            if ((lane & 15) == 0) st_rlx(&g_rs[srow], ~epoch, 0, 0, 0);
            if (threadIdx.x < 4) st_rlx(&g_m1[bid * 4 + lane], ~epoch, 0, 0, 0);
            float a[8];
#pragma unroll
            for (int k = 0; k < 8; ++k) a[k] = 0.f;
            fma8(a, silu_bf(bf_lo(cv)), wv0);
            fma8(a, silu_bf(bf_hi(cv)), wv1);
            red8(a, lane);
            float* red = (float*)(smem + RED_OFF);
            if ((lane & 2) == 0) red[w * 16 + (lane & 1) * 8 + (lane >> 2)] = a[0];
            float sm = 0.f, sq = 0.f;
#pragma unroll
            for (int i = 0; i < 4; ++i) { sumsq(xs[i].x, sm, sq); sumsq(xs[i].y, sm, sq); sumsq(xs[i].z, sm, sq); sumsq(xs[i].w, sm, sq); }
#pragma unroll
            for (int o = 1; o < 16; o <<= 1) { sm += __shfl_xor_sync(~0u, sm, o); sq += __shfl_xor_sync(~0u, sq, o); }
            uint32_t rs, nm;
            row_stats(sm, sq, rs, nm);
            PROF(16);
            par = epoch & 1u;
            *s_epoch = epoch;
            bar_sync(0, 288);
            if (threadIdx.x == 64) asm volatile("red.relaxed.gpu.global.add.u32 [%0], 1;" ::"l"(&g_cnt) : "memory");
            if (w == 1 && elect()) prefetch_l2((const char*)wqkv + bid * 12288, 12288);
            if ((lane & 15) == 0) st_rlx(&g_rs[srow], par, rs, nm, 0u);
            if (w == 0) {
                float4 v = *(const float4*)(red + 4 * lane);
#pragma unroll
                for (int o = 4; o < 32; o <<= 1) {
                    v.x += __shfl_xor_sync(~0u, v.x, o); v.y += __shfl_xor_sync(~0u, v.y, o);
                    v.z += __shfl_xor_sync(~0u, v.z, o); v.w += __shfl_xor_sync(~0u, v.w, o);
                }
                if (lane < 4) st_rlx(&g_m1[bid * 4 + lane], tagw(f2u(v.x), par), f2u(v.y), f2u(v.z), f2u(v.w));
            }
            PROF(0);
            asm volatile("setmaxnreg.inc.sync.aligned.u32 232;");
            uint4 pv[4];
            const uint4* mp = &g_m1[(threadIdx.x >> 2) * 8 + t];
            {
                const uint32_t xa = sb + 3 * STAGE_BYTES + (16 * w + (lane & 15)) * 128 + (((lane >> 4) ^ lane) & 7) * 16;
#pragma unroll
                for (int i = 0; i < 8; ++i) {
                    if ((i & 3) == 0) mbar_wait(bars + 8 * (B_XF + (i >> 2)), 0);
#pragma unroll
                    for (int c = 0; c < 4; ++c) A[4 * i + c] = ldsm4((xa ^ (c * 32)) + i * STAGE_BYTES);
                }
#pragma unroll
                for (int c = 0; c < 4; ++c) xs[c] = ldsm4((xa ^ (c * 32)) + r * STAGE_BYTES);
            }
            PROF(15);
#pragma unroll 1
            do {
                if (SLP0) __nanosleep(SLP0);
                pv[0] = ld_rlx(mp); pv[1] = ld_rlx(mp + 4);
                pv[2] = ld_rlx(&g_rs[row0]); pv[3] = ld_rlx(&g_rs[row0 + 8]);
            } while (stale<4>(pv, par));
            mbar_arrive1(bars + 8 * B_GO);
#pragma unroll
            for (int c = 0; c < 4; ++c) st_rlx(XR2(4 * r, X_XR + c), xs[c].x, xs[c].y, xs[c].z, xs[c].w);
            const int i = threadIdx.x & 127;
            uint32_t v0 = pack2(u2f(pv[0].x) + u2f(pv[1].x), u2f(pv[0].y) + u2f(pv[1].y));
            uint32_t v1 = pack2(u2f(pv[0].z) + u2f(pv[1].z), u2f(pv[0].w) + u2f(pv[1].w));
            if (w >= 4) { v0 = one_plus(v0); v1 = one_plus(v1); }
            uint32_t* tp = (uint32_t*)(smem + TAB1_OFF) + (i >> 2) * 16 + (i & 1) * 8 + ((i >> 1) & 1) + (w >= 4 ? 0 : 2);
            tp[0] = v0; tp[4] = v1;
            ln.rs0 = pv[2].y; ln.nm0 = pv[2].z; ln.rs1 = pv[3].y; ln.nm1 = pv[3].z;
            bar_sync(1, 256);
        }
        PROF(1);

#pragma unroll 1
        for (int ph = 0; ph < 3; ++ph) {
            float acc[64];
            {
                const uint32_t tab = sb + (ph ? TAB2_OFF : TAB1_OFF) + t * 16;
                if (ph == 1) {
                    uint4 sv[2];
                    poll<2>(sv, XROW(X_ST) - lane + 16 * t + g, [](int i) { return 8 * i; }, par);
#pragma unroll
                    for (int i = 0; i < NB1; ++i) A[i] = ld_rlx(XROW(X_X1 + i));
                    float q0 = u2f(sv[0].x) + u2f(sv[1].x), s0 = u2f(sv[0].y) + u2f(sv[1].y);
                    float q1 = u2f(sv[0].z) + u2f(sv[1].z), s1 = u2f(sv[0].w) + u2f(sv[1].w);
#pragma unroll
                    for (int o = 1; o < 4; o <<= 1) {
                        s0 += __shfl_xor_sync(~0u, s0, o); q0 += __shfl_xor_sync(~0u, q0, o);
                        s1 += __shfl_xor_sync(~0u, s1, o); q1 += __shfl_xor_sync(~0u, q1, o);
                    }
                    row_stats(s0, q0, ln.rs0, ln.nm0);
                    row_stats(s1, q1, ln.rs1, ln.nm1);
                    validate<NB1>(A, XROW(X_X1), [](int i) { return 32 * i; }, par);
#pragma unroll
                    for (int i = NB1; i < 32; ++i) A[i] = ld_rlx(XROW(X_X1 + i));
                    bar_sync_if(w < 4, 2, 256);
                    PROF(7);
                }
                uint4 cs[4];
#pragma unroll
                for (int c = 0; c < 4; ++c) cs[c] = lds128(tab + c * 64);
#pragma unroll
                for (int i = 0; i < 8; ++i) {
                    const int slot = ph == 2 ? (8 + i) % NSTAGE : i, prev = ph == 2 ? (6 + i) % NSTAGE : i - 2;
                    if (4 * i == NB1 && ph == 1) validate<32 - NB1>(&A[NB1], XROW(X_X1 + NB1), [](int i) { return 32 * i; }, par);
                    if (ph < 2) {
#pragma unroll
                        for (int c = 0; c < 4; ++c) ln_mod(A[4 * i + c], cs[c], ln);
                        if (i < 7) {
#pragma unroll
                            for (int c = 0; c < 4; ++c) cs[c] = lds128(tab + (4 * i + 4 + c) * 64);
                        }
                    }
                    mbar_wait(bars + 8 * (B_FULL + slot), (i >= 3 && ph == 2) ? 1 : 0);
                    const uint64_t d = DB0(gridDim.z - 1) + slot * 1024;
                    WG_FENCE();
#pragma unroll
                    for (int c = 0; c < 4; ++c) {
                        if (i == 0 && c == 0) wgmma128<0>(acc, A[4 * i + c], d);
                        else wgmma128<1>(acc, A[4 * i + c], d + c * 128);
                    }
                    WG_COMMIT();
                    if (i > 1) {
                        WG_WAIT(2);
                        RELEASE(prev, 1);
                    }
                }
                WG_WAIT(0);
                pin<64>(acc);
                RELEASE(ph == 2 ? 3 : 6, 2);
            }
            if (ph) {
                uint4 hv[4];
#pragma unroll
                for (int c = 0; c < 4; ++c) { hv[c] = gate8(&acc[8 * c], &acc[32 + 8 * c]); hv[c].x = tagw(hv[c].x, par); }
#pragma unroll
                for (int c = 0; c < 4; ++c) st_rlx(XR2(r * 12 + 4 * ph, X_HH - 4 + c), hv[c].x, hv[c].y, hv[c].z, hv[c].w);
                PROF(7 + ph);
                continue;
            }
            PROF(2);
            uint4 qf;
            const uint32_t qs = sb + OUT_OFF + threadIdx.x * 16;
            {
                bar_sync(1, 256);
                pin<64>(acc);
                const uint32_t kvw = sb + KV_OFF + (16 + w) * 1024 + ((lane >> 3) & 1) * 512 + (lane >> 4) * 128 + (lane & 7) * 16;
                const uint32_t km = t ? ~0u : ~1u, kp = t ? 0u : par;
#pragma unroll
                for (int i = 0; i < 8; ++i) {
                    const uint4 v = pack8(&acc[8 * i]);
                    stsm4(kvw + (i & 3) * 24576 + (i >> 2) * 256, (v.x & km) | kp, (v.y & km) | kp, (v.z & km) | kp, (v.w & km) | kp);
                }
                if (w < 4) {
                    const uint32_t id = (2 * t == g ? 0x3f80u : 0u) | (2 * t + 1 == g ? 0x3f800000u : 0u);
                    *(uint32_t*)(smem + ONES_OFF + threadIdx.x * 4) = (w & 1) ? id : w ? 0u : 0x3f803f80u;
                }
                if (__builtin_expect(j < 2, 0)) {
#pragma unroll 1
                    for (int i = 0; i < 8 * (2 - j); ++i)
                        sts128(sb + KV_OFF + (i & 3) * 24576 + (i >> 2) * 4096 + threadIdx.x * 16, 0, 0, 0, 0);
                }
                fence_async_smem();
                __syncwarp();
                mbar_arrive1(bars + 8 * B_KVW);
                PROF(17);
                float accq[32];
#pragma unroll
                for (int q = 0; q < 4; ++q) {
                    const int slot = (8 + q) % NSTAGE;
                    mbar_wait(bars + 8 * (B_FULL + slot), q == 3 ? 1 : 0);
                    const uint64_t d = DB0(blockIdx.y) + slot * 1024;
                    WG_FENCE();
#pragma unroll
                    for (int s = 0; s < 8; ++s) {
                        if (q == 0 && s == 0) wgmma64<0>(accq, A[8 * q + s], d);
                        else wgmma64<1>(accq, A[8 * q + s], d + s * 128);
                    }
                }
                WG_COMMIT();
                WG_WAIT(0);
                pin<32>(accq);
                RELEASE(8, 3); RELEASE(0, 1);
#pragma unroll
                for (int i = 0; i < 32; ++i) accq[i] *= 0.25f * 1.4426950408889634f;
                qf = pack8(accq);
#pragma unroll
                for (int h = 1; h < 4; ++h) {
                    const uint4 v = pack8(&accq[8 * h]);
                    sts128(qs + (h - 1) * 4096, v.x, v.y, v.z, v.w);
                }
            }
            PROF(3);
            uint4* const st_own = XROW(X_ST) - lane + r * 8 + g;

            {
                const int wg = w >> 2, w4 = w & 3;
                const bool pC = 2 * t <= g, pD = 2 * t + 1 <= g;
                const uint32_t mD = (pC ? 0xffffu : 0u) | (pD ? 0xffff0000u : 0u);
                const uint32_t lk = sb + KV_OFF + w4 * 1024 + (lane >> 4) * 512 + ((lane >> 3) & 1) * 128 + (lane & 7) * 16;
                const uint32_t lv = sb + KV_OFF + w4 * 1024 + ((lane >> 3) & 1) * 512 + (lane >> 4) * 128 + (lane & 7) * 16 + 256;
                st_rlx(XR2(4 * r, X_O + 2), par ^ 1u, 0, 0, 0);
                st_rlx(XR2(4 * r, X_O + 3), par ^ 1u, 0, 0, 0);
                if (t == 0) st_rlx(st_own, par ^ 1u, 0, 0, 0);
                bar_sync(1, 256);
                bar_sync_if(wg == 0, 2, 256);
                uint32_t units = wg ? UNITS1 : UNITS0;
#pragma unroll 1
                while (true) {
                    const int h = units & 3, hf = (units >> 2) & 1;
                    const int b0 = 16 - 8 * j - 4 * hf - w4;
                    const uint32_t ka = lk + h * 24576 + hf * 4096, va = lv + h * 24576 + hf * 4096;
                    const uint4 qn = lds128(qs + (((units >> 4) & 3) - 1) * 4096 + (((units >> 6) & 1) - wg) * 2048);
                    mbar_wait(bars + 8 * (B_HALO + h), 0);
                    if (h == 0) PROF(18);
                    float O[8], L[4];
#pragma unroll
                    for (int b = 1; b < 16; ++b) {
                        float S[8];
                        mma2<0>(S, qf, ldsm4(ka + b * 1024));
                        const uint4 P = exp_pack(S);
                        const uint32_t on = b < b0 ? 0u : 0x3f803f80u;
                        if (b == 1) { mma2<0>(O, P, ldsm4t(va + b * 1024)); mma2<0, 1>(L, P, make_uint4(on, on, 0u, 0u)); }
                        else { mma2<1>(O, P, ldsm4t(va + b * 1024)); mma2<1, 1>(L, P, make_uint4(on, on, 0u, 0u)); }
                        if (b == 8) {
                            float N[8];
                            mma2<0>(S, qf, ldsm4(ka + 16384));
                            mma2<0>(N, qf, ldsm4(ka));
                            S[0] = pC ? S[0] : N[0]; S[1] = pD ? S[1] : N[1]; S[4] = N[4]; S[5] = N[5];
                            S[6] = pC ? S[6] : N[6]; S[7] = pD ? S[7] : N[7];
                            const uint4 Q = exp_pack(S);
                            const uint4 Po = make_uint4(Q.x & ~mD, 0u, Q.z, Q.w & ~mD), Pn = make_uint4(Q.x & mD, Q.y, 0u, Q.w & mD);
                            const uint32_t o0 = b0 > 0 ? 0u : 0x3f803f80u;
                            mma2<1>(O, Pn, ldsm4t(va + 16384));
                            mma2<1, 1>(L, Pn, make_uint4(0x3f803f80u, 0x3f803f80u, 0u, 0u));
                            mma2<1>(O, Po, ldsm4t(va));
                            mma2<1, 1>(L, Po, make_uint4(o0, o0, 0u, 0u));
                            bar_arrive_if((units & 7) == 4, 2, 256);
                        }
                    }
                    if (__builtin_expect(__any_sync(~0u, (f2u(L[0]) >> 23) - 47u > 160u || (f2u(L[2]) >> 23) - 47u > 160u), 0)) {
                        float m0 = -3e38f, m1 = -3e38f;
#pragma unroll 1
                        for (int pass = 0; pass < 2; ++pass) {
#pragma unroll
                            for (int i = 0; i < 8; ++i) O[i] = 0.f;
#pragma unroll
                            for (int i = 0; i < 4; ++i) L[i] = 0.f;
#pragma unroll 1
                            for (int b = max(b0, 0); b <= 16; ++b) {
                                float S[8];
                                mma2<0>(S, qf, ldsm4(ka + b * 1024));
                                const bool dg = b == 16, od = b == 0;
                                if ((dg && !pC) || (od && pC)) S[0] = S[6] = -3e38f;
                                if ((dg && !pD) || (od && pD)) S[1] = S[7] = -3e38f;
                                if (od) S[2] = S[3] = -3e38f;
                                if (dg) S[4] = S[5] = -3e38f;
                                if (pass == 0) { maxb<1>(S, m0, m1); continue; }
#pragma unroll
                                for (int i = 0; i < 8; ++i) S[i] -= (i & 2) ? m1 : m0;
                                const uint4 P = exp_pack(S);
                                mma2<1>(O, P, ldsm4t(va + b * 1024));
                                mma2<1, 1>(L, P, make_uint4(0x3f803f80u, 0x3f803f80u, 0u, 0u));
                            }
#pragma unroll
                            for (int o = 1; o < 4; o <<= 1) { m0 = fmaxf(m0, __shfl_xor_sync(~0u, m0, o)); m1 = fmaxf(m1, __shfl_xor_sync(~0u, m1, o)); }
                        }
                    }
                    const float i0 = rcpf(L[0]), i1 = rcpf(L[2]);
                    st_rlx(XR2(4 * r + h + (hf - wg) * 4 * X_ROWS, X_O), tagw(pack2(O[0] * i0, O[1] * i0), par), pack2(O[2] * i1, O[3] * i1),
                           pack2(O[4] * i0, O[5] * i0), pack2(O[6] * i1, O[7] * i1));
                    mbar_arrive_lt(bars + 8 * (B_EMPTY + 1 + h + (h >> 1) + lane), lane, h < 3 ? 1 + (h & 1) : 0);
                    qf = qn;
                    units = __shfl_sync(~0u, units >> 4, 0);
                    if (units < 16) break;
                    PROF(19 + (h > 2 ? 2 : h));
                }
            }
            PROF(4);

            {
                uint4 xr[4];
#pragma unroll
                for (int c = 0; c < 4; ++c) xr[c] = ld_rlx(XR2(4 * r, X_XR + c));
                float acc[32];
#pragma unroll
                for (int m = 0; m < 4; ++m) mbar_wait(bars + 8 * (B_FULL + 7 + m), 1);
                const uint64_t d0 = DB0(blockIdx.z) + 7 * 1024;
#pragma unroll
                for (int h = 0; h < 4; ++h) {
                    if ((h & 1) == 0) {
                        poll<16>(&A[8 * h], XROW(X_O + h), [](int i) { return 128 * (i & 7) + 32 * (i >> 3); }, par);
                        WG_FENCE();
                    }
#pragma unroll
                    for (int i = 0; i < 8; ++i) {
                        if (h == 0 && i == 0) wgmma64<0>(acc, A[8 * h + i], d0);
                        else wgmma64<1>(acc, A[8 * h + i], d0 + i * 512 + h * 128);
                    }
                }
                WG_COMMIT();
                RELEASE(5, 2);
                mbar_wait(bars + 8 * B_TAB2, 0);
                WG_WAIT(0);
                pin<32>(acc);
                RELEASE(7, 4);
                bar_arrive_if(w >= 4, 2, 256);
                PROF(5);
                float s0 = 0.f, s1 = 0.f, q0 = 0.f, q1 = 0.f;
                uint32_t xo[16];
#pragma unroll
                for (int b = 0; b < 8; ++b) {
                    const float2 ga = *(const float2*)(smem + GA_OFF + (8 * b + 2 * t) * 4);
                    const uint32_t u0 = (b & 1) ? xr[b >> 1].z : xr[b >> 1].x, u1 = (b & 1) ? xr[b >> 1].w : xr[b >> 1].y;
                    const float v0 = fmaf(ga.x, acc[4 * b], bf_lo(u0)), v1 = fmaf(ga.y, acc[4 * b + 1], bf_hi(u0));
                    const float v2 = fmaf(ga.x, acc[4 * b + 2], bf_lo(u1)), v3 = fmaf(ga.y, acc[4 * b + 3], bf_hi(u1));
                    xo[2 * b] = pack2(v0, v1);
                    xo[2 * b + 1] = pack2(v2, v3);
                    s0 += v0 + v1; q0 = fmaf(v0, v0, fmaf(v1, v1, q0));
                    s1 += v2 + v3; q1 = fmaf(v2, v2, fmaf(v3, v3, q1));
                }
                sts128(qs, xo[0], xo[4], xo[8], xo[12]);
#pragma unroll
                for (int i = 0; i < 4; ++i) xo[4 * i] = tagw(xo[4 * i], par);
#pragma unroll
                for (int i = 0; i < 4; ++i) st_rlx(XR2(4 * r, X_X1 + i), xo[4 * i], xo[4 * i + 1], xo[4 * i + 2], xo[4 * i + 3]);
#pragma unroll
                for (int o = 1; o < 4; o <<= 1) {
                    s0 += __shfl_xor_sync(~0u, s0, o); q0 += __shfl_xor_sync(~0u, q0, o);
                    s1 += __shfl_xor_sync(~0u, s1, o); q1 += __shfl_xor_sync(~0u, q1, o);
                }
                if (t == 0) st_rlx(st_own, tagw(f2u(q0), par), f2u(s0), f2u(q1), f2u(s1));
            }
            PROF(6);
            ln.rs0 = ln.nm0 = ln.rs1 = ln.nm1 = 0;
        }
        const uint4* const hp = XR2((r & 6) * 12, X_HH);
        auto off8 = [](int k) { return ((k >> 2) * 12 + (k & 3)) * 32; };
        {
            float ag[24], au[24];
#pragma unroll
            for (int i = 0; i < 8; ++i) {
                const int n = 38 + i;
                mbar_wait(bars + 8 * (B_FULL + n % NSTAGE), (n / NSTAGE) & 1);
                const uint64_t d = DB0(gridDim.y - 1) + (n % NSTAGE) * 1024;
                WG_FENCE();
#pragma unroll
                for (int c = 0; c < 4; ++c) {
                    if (i == 0 && c == 0) {
                        wgmma48<0>(ag, A[4 * i + c], d);
                        wgmma48<0>(au, A[4 * i + c], d + 512);
                    } else {
                        wgmma48<1>(ag, A[4 * i + c], d + c * 128);
                        wgmma48<1>(au, A[4 * i + c], d + 512 + c * 128);
                    }
                }
                WG_COMMIT();
                if (i < 3) st_rlx(XR2(r * 12, X_HH + 8 + i), par ^ 1u, 0, 0, 0);
                else if (i < 7) st_rlx(XR2(((r + 6) & 7) * 12, X_PT + 5 + i), par ^ 1u, 0, 0, 0);
                if (i > 0) {
                    WG_WAIT(1);
                    RELEASE((n - 1) % NSTAGE, 1);
                }
                if (i == 2 || i == 4) {
#pragma unroll
                    for (int c = 0; c < 8; ++c) A[4 * i - 8 + c] = ld_rlx(hp + 64 * (i - 2) + off8(c));
                }
            }
            WG_WAIT(0);
            pin<24>(ag); pin<24>(au);
            RELEASE(45 % NSTAGE, 1);
#pragma unroll
            for (int c = 0; c < 3; ++c) A[16 + c] = gate8(&ag[8 * c], &au[8 * c]);
        }
        PROF(10);
        {
            float acc[32];
            uint4 P[4], Q[12], X1[4];
            int slot = 46 % NSTAGE, fpar = 0;
            uint4* dst = xb;
#pragma unroll
            for (int c = 0; c < 3; ++c) {
                A[16 + c].x = tagw(A[16 + c].x, par);
                st_rlx(XR2(r * 12, X_HH + 8 + c), A[16 + c].x, A[16 + c].y, A[16 + c].z, A[16 + c].w);
            }
            P[0] = P[1] = P[2] = P[3] = make_uint4(0, 0, 0, 0);
#pragma unroll 1
            for (int cb = 0; cb < 4; ++cb) {
                if (cb == 0) validate<16>(A, hp, [](int k) { return (((k >> 2) & 1) * 12 + (k & 3) + (k >> 3) * 4) * 32; }, par);
                uint64_t d;
#pragma unroll
                for (int p = 0; p < 3; ++p) {
                    mbar_wait(bars + 8 * (B_FULL + slot), fpar);
                    d = DB0(blockDim.y - 1) + slot * 1024;
                    if (++slot == NSTAGE) { slot = 0; fpar = 1; }
                    WG_FENCE();
#pragma unroll
                    for (int k = 0; k < (p < 2 ? 8 : 3); ++k) {
                        if (p == 0 && k == 0) wgmma64<0>(acc, A[k], d);
                        else if (p < 2) wgmma64<1>(acc, A[8 * p + k], d + k * 128);
                        else wgmma64<1>(acc, A[16 + k], d + (r & 1) * 512 + k * 128);
                    }
                    if (p == 0 && cb > 0) {
#pragma unroll
                        for (int c = 0; c < 4; ++c) st_rlx(dst + c * 32, P[c].x, P[c].y, P[c].z, P[c].w);
                    }
                }
                if (cb == 0) poll<3>(&A[19], XR2((r ^ 1) * 12, X_HH + 8), [](int c) { return 32 * c; }, par);
                WG_FENCE();
#pragma unroll
                for (int k = 0; k < 3; ++k) wgmma64<1>(acc, A[19 + k], d + (~r & 1) * 512 + k * 128);
                WG_COMMIT();
                if (cb == 3) {
#pragma unroll
                    for (int i = 0; i < 4; ++i) X1[i] = ld_rlx(XR2(4 * r, X_X1 + i));
#pragma unroll
                    for (int i = 0; i < 8; ++i) Q[i] = ld_rlx(XR2(r * 12, X_PT + i));
                }
                WG_WAIT(0);
                pin<32>(acc);
                if (cb == 3) break;
                if (cb == 0) RELEASE(46 % NSTAGE, 1);
                dst = XR2(((r + 2 + 2 * cb) & 7) * 12 + 4 * cb, X_PT);
#pragma unroll
                for (int c = 0; c < 4; ++c) { P[c] = pack8(&acc[8 * c]); P[c].x = tagw(P[c].x, par); }
            }
            const uint64_t did = cdesc(sb + ONES_OFF + 128, 128, 128);
            {
                const uint4 e = lds128(sb + OUT_OFF + threadIdx.x * 16);
                X1[0].x = e.x; X1[1].x = e.y; X1[2].x = e.z; X1[3].x = e.w;
            }
            PROF(11);
            validate<8>(Q, XR2(r * 12, X_PT), [](int i) { return 32 * i; }, par);
            poll<4>(Q + 8, XR2(r * 12, X_PT + 8), [](int i) { return 32 * i; }, par);
            float ap[4][8];
            WG_FENCE();
#pragma unroll
            for (int i = 0; i < 12; ++i) {
                if (i < 4) wgmma16<0>(ap[i], Q[i], did);
                else wgmma16<1>(ap[i & 3], Q[i], did);
            }
            WG_COMMIT();
            WG_WAIT(0);
            pin<32>(&ap[0][0]);
            PROF(13);
            const uint32_t stg = sb + OUT_OFF + 4096 + w * 1024;
            uint32_t ln2;
            asm volatile("mov.u32 %0, %%laneid;" : "=r"(ln2));
            char* const op = (char*)out + (size_t)(128 * j + 16 * w) * 1024 + 128 * r + (ln2 >> 2) * 1024 + (ln2 & 3) * 16;
            const int wr = (lane & 7) + (lane & 8), rr = lane >> 2;
#pragma unroll
            for (int hf = 0; hf < 2; ++hf) {
#pragma unroll
                for (int i = 2 * hf; i < 2 * hf + 2; ++i) {
                    const uint32_t xw[4] = {X1[i].x, X1[i].y, X1[i].z, X1[i].w};
                    uint32_t o[4];
#pragma unroll
                    for (int e = 0; e < 4; ++e) {
                        const float2 gb = *(const float2*)(smem + GB_OFF + (16 * i + 8 * (e >> 1) + 2 * t) * 4);
                        o[e] = pack2(fmaf(gb.x, acc[8 * i + 2 * e] + ap[i][2 * e], bf_lo(xw[e])),
                                     fmaf(gb.y, acc[8 * i + 2 * e + 1] + ap[i][2 * e + 1], bf_hi(xw[e])));
                    }
                    stsm4(stg + wr * 64 + (((2 * (i & 1) + (lane >> 4)) ^ (wr >> 1)) & 3) * 16, o[0], o[1], o[2], o[3]);
                }
                __syncwarp();
#pragma unroll
                for (int k = 0; k < 2; ++k) {
                    const uint4 v = lds128(stg + (rr + 8 * k) * 64 + ((t ^ (rr >> 1)) & 3) * 16);
                    *(uint4*)(op + k * 8192 + 64 * hf) = v;
                }
                __syncwarp();
            }
            mbar_arrive1(bars + 8 * B_DONE);
        }
        PROF(12);
        PROF_DUMP();
    } else {
        asm volatile("setmaxnreg.dec.sync.aligned.u32 40;");
        if (warp == 8) {
            uint4 tb[2];
            tb[0] = __ldg(&c_sched[lane]); tb[1] = __ldg(&c_sched[32 + lane]);
#pragma unroll
            for (int q = 0; q < 2; ++q) {
                const uint32_t c = ((tb[q].x & 0xffffu) + (tb[q].y & 255u) * r) & (tb[q].y >> 16);
                const uint32_t cr = c + (((tb[q].x >> 16) + ((tb[q].y >> 8) & 255u) * (r & 6)) << 16);
                if (q == 0 || lane < 26) sts128(sb + SCHED_OFF + q * 512 + lane * 16, cr, cr + tb[q].z, tb[q].w, 0);
            }
            __syncwarp();
            PROF(2);
            PROF_DUMP();
            bar_arrive(3, 128);
        } else {
            bar_sync(3, 128);
            mbar_wait(bars + 8 * B_GO, 0);
            const unsigned epoch = *s_epoch;
            if (warp < 11) {
                const int nn = j < 2 ? j : 2;
                const unsigned* fl = (const unsigned*)(g_kv + (size_t)(bid - 8 * (lane + 1)) * 2048 + 511);
                unsigned fv = epoch, fv2 = epoch;
                if (lane < nn) { fv = ld_u32(fl + (10 - warp) * 2048); fv2 = ld_u32(fl + (12 - warp) * 2048); }
                mbar_wait(bars + 8 * B_KVW, 0);
                if (warp == 9 && elect()) {
                    if (j < 15) {
#pragma unroll 1
                        for (int h = 0; h < 4; ++h) {
                            bulk_s2g(g_kv + (size_t)bid * 2048 + h * 512, sb + KV_OFF + h * 24576 + 16384, 8192);
                            if (h < 2) __nanosleep(PUBGAP);
                        }
                        asm volatile("cp.async.bulk.commit_group;" ::: "memory");
                    }
                }
                PROF(1);
                uint32_t lph = 0;
#pragma unroll 1
                for (int h = 10 - warp; h < 4;) {
#pragma unroll 1
                    while ((fv ^ epoch) & 1u) fv = ld_u32(fl + h * 2048);
                    __syncwarp();
                    if (h < 2) { if (lph == 0) PROF(8); else PROF(10); }
                    if (elect()) {
                        mbar_expect(bars + 8 * (B_HLD + h), nn * 8192);
#pragma unroll 1
                        for (int n = 1; n <= nn; ++n)
                            bulk_g2s(sb + KV_OFF + h * 24576 + (2 - n) * 8192, g_kv + (size_t)(bid - 8 * n) * 2048 + h * 512, 8192,
                                     bars + 8 * (B_HLD + h));
                    }
                    mbar_wait(bars + 8 * (B_HLD + h), lph);
                    if (h < 2 && lph == 0) PROF(9);
                    uint32_t bad = 0;
#pragma unroll 1
                    for (int n = 1; n <= nn; ++n) {
#pragma unroll
                        for (int i = 0; i < 16; ++i) bad |= lds32(sb + KV_OFF + h * 24576 + (2 - n) * 8192 + lane * 16 + i * 512) ^ epoch;
                    }
                    if (__any_sync(~0u, bad & 1u)) { lph ^= 1; continue; }
                    mbar_arrive1(bars + 8 * (B_HALO + h));
                    PROF(3 + h);
                    lph = 0;
                    h += 2;
                    fv = fv2;
                }
                if (warp == 9) {
                    asm volatile("cp.async.bulk.wait_group.read 0;" ::: "memory");
                    __syncwarp();
                    mbar_arrive1(bars + 8 * B_PUB);
                }
                PROF(2);
                PROF_DUMP();
            } else {
                const uint32_t par = epoch & 1u;
                if (lane < 8) {
                    const char* p = lane < 4 ? (const char*)(wmod + (size_t)(4 * bid + lane) * 3072 + 1024)
                                  : lane == 4 ? (const char*)wo + bid * 4096
                                  : (const char*)(lane == 5 ? wg : lane == 6 ? wu : wd) + bid * 11008;
                    prefetch_l2(p, lane < 5 ? 4096 : 11008);
                }
                mbar_wait(bars + 8 * (B_FULL + 5), 0);
                {
                    const int half = lane & 1, rg = lane >> 1;
                    float a[8];
#pragma unroll
                    for (int k = 0; k < 8; ++k) a[k] = 0.f;
#pragma unroll 1
                    for (int b = 0; b < 8; ++b) {
                        const int row = b * 64 + rg * 4;
                        uint4 wv[4];
#pragma unroll
                        for (int i = 0; i < 4; ++i) wv[i] = ldg_nc(wmod + (size_t)(row + i) * 3072 + 1024 + 16 * bid + 8 * half);
                        const uint2 cv = *(const uint2*)(cvec + row);
                        fma8(a, silu_bf(bf_lo(cv.x)), wv[0]); fma8(a, silu_bf(bf_hi(cv.x)), wv[1]);
                        fma8(a, silu_bf(bf_lo(cv.y)), wv[2]); fma8(a, silu_bf(bf_hi(cv.y)), wv[3]);
                    }
                    red8(a, lane);
                    float* red2 = (float*)(smem + RED_OFF + 512);
                    if ((lane & 2) == 0) red2[half * 8 + (lane >> 2)] = a[0];
                    __syncwarp();
                    if (lane < 4) {
                        const uint4 v = *(const uint4*)(red2 + 4 * lane);
                        st_rlx(&g_m2[4 * bid + lane], tagw(v.x, par), v.y, v.z, v.w);
                    }
                    __syncwarp();
                }
                PROF(1);
                uint32_t* tab2 = (uint32_t*)(smem + TAB2_OFF);
#pragma unroll 1
                for (int q = 0; q < 9; ++q) {
                    const int e = q < 8 ? 128 + q * 32 + lane : (lane < 16 ? 16 * r + lane : 368 + 16 * r + lane);
                    uint4 v;
                    poll<1>(&v, &g_m2[e], [](int) { return 0; }, par);
                    uint32_t v0 = pack2(u2f(v.x), u2f(v.y)), v1 = pack2(u2f(v.z), u2f(v.w));
                    if (q < 8) {
                        const int ep = (q & 3) * 64 + lane * 2;
                        const int isc = q >> 2;
                        if (isc) { v0 = one_plus(v0); v1 = one_plus(v1); }
                        const int kap = ep >> 3, wi = ep & 7;
                        const int o0 = (kap * 4 + (wi & 3)) * 4 + (wi >> 2) + (isc ? 0 : 2);
                        tab2[o0] = v0;
                        tab2[o0 + 4] = v1;
                    } else {
                        *(float4*)(smem + GA_OFF + lane * 16) = make_float4(bf_lo(v0), bf_hi(v0), bf_lo(v1), bf_hi(v1));
                    }
                }
                __syncwarp();
                if (lane == 0) mbar_arrive(bars + 8 * B_TAB2);
                PROF(2);
                PROF_DUMP();
            }
        }
        if (warp < 11 && elect()) {
            uint32_t a = sb + SCHED_OFF + (warp == 8 ? 0 : (10 + warp) * 16);
            uint4 en = lds128(a);
#pragma unroll 1
            while (a < sb + SCHED_OFF + 58 * 16) {
                const uint4 e = en;
                a += a < sb + SCHED_OFF + 18 * 16 ? 16 : 48;
                en = lds128(a);
                const uint32_t slot = e.z & 15u, fb = bars + 8 * B_FULL + 8 * slot, dst = sb + slot * STAGE_BYTES;
                if (e.z & 0xff00u) mbar_wait_b(bars + ((e.z >> 5) & 0x7f8u), 0);
                mbar_wait_b(fb + 8 * (B_EMPTY - B_FULL), (e.z >> 5) & 1u);
                mbar_expect(fb, (e.z << 10) & STAGE_BYTES);
                if (e.z & 16u) {
                    tma2d(dst, &tm.m[(e.z >> 16) & 15u], e.x & 0xffffu, e.x >> 16, fb);
                    tma2d(dst + 8192, &tm.m[e.z >> 24], e.y & 0xffffu, e.y >> 16, fb);
                }
            }
            mbar_wait_b(bars + 8 * B_DONE, 0);
        }
    }
}

typedef CUresult (*EncodeFn)(CUtensorMap*, CUtensorMapDataType, cuuint32_t, void*, const cuuint64_t*, const cuuint64_t*,
                             const cuuint32_t*, const cuuint32_t*, CUtensorMapInterleave, CUtensorMapSwizzle,
                             CUtensorMapL2promotion, CUtensorMapFloatOOBfill);

void make2d(EncodeFn enc, CUtensorMap* m, const void* p, uint64_t cols, uint64_t rows, uint32_t box_rows = 64) {
    cuuint64_t dims[2] = {cols, rows};
    cuuint64_t str[1] = {cols * 2};
    cuuint32_t box[2] = {64, box_rows}, es[2] = {1, 1};
    enc(m, CU_TENSOR_MAP_DATA_TYPE_BFLOAT16, 2, (void*)p, dims, str, box, es, CU_TENSOR_MAP_INTERLEAVE_NONE,
        CU_TENSOR_MAP_SWIZZLE_128B, CU_TENSOR_MAP_L2_PROMOTION_L2_128B, CU_TENSOR_MAP_FLOAT_OOB_FILL_NONE);
}

}

extern "C" void kernel_launch(void* const* d_in, const int* in_sizes, int n_in, void* d_out, int out_size) {
    const __nv_bfloat16* x = (const __nv_bfloat16*)d_in[0];
    const __nv_bfloat16* wqkv = (const __nv_bfloat16*)d_in[1];
    const __nv_bfloat16* wo = (const __nv_bfloat16*)d_in[2];
    const __nv_bfloat16* wg = (const __nv_bfloat16*)d_in[4];
    const __nv_bfloat16* wu = (const __nv_bfloat16*)d_in[5];
    const __nv_bfloat16* wd = (const __nv_bfloat16*)d_in[6];
    const __nv_bfloat16* c = (const __nv_bfloat16*)d_in[7];
    const __nv_bfloat16* wmod = (const __nv_bfloat16*)d_in[8];

    void* fn = nullptr;
    cudaDriverEntryPointQueryResult qr;
    cudaGetDriverEntryPoint("cuTensorMapEncodeTiled", &fn, cudaEnableDefault, &qr);
    EncodeFn enc = (EncodeFn)fn;
    Maps tm;
    make2d(enc, &tm.m[0], x, 512, 2048, 128);
    make2d(enc, &tm.m[1], wqkv, 1536, 512);
    make2d(enc, &tm.m[2], wo, 512, 512);
    make2d(enc, &tm.m[3], wg, 1376, 512);
    make2d(enc, &tm.m[4], wu, 1376, 512);
    make2d(enc, &tm.m[5], wd, 512, 1376);
    cudaFuncSetAttribute(fused_kernel, cudaFuncAttributeMaxDynamicSharedMemorySize, SMEM_BYTES + PROF_EXTRA);
    fused_kernel<<<128, 384, SMEM_BYTES + PROF_EXTRA, cudaStreamPerThread>>>(x, wqkv, wo, wg, wu, wd, c, wmod, (__nv_bfloat16*)d_out, tm);
}
```

```cpp
#include <cuda_runtime.h>
#include <cuda_bf16.h>
#include <cuda.h>
#include <stdint.h>

namespace {

constexpr int NSTAGE = 11;
constexpr int STAGE_BYTES = 16384;
constexpr int KV_OFF = 1 * STAGE_BYTES;
constexpr int OUT_OFF = NSTAGE * STAGE_BYTES;
constexpr int TAB1_OFF = OUT_OFF + 12288;
constexpr int TAB2_OFF = TAB1_OFF + 2048;
constexpr int GA_OFF = TAB2_OFF + 2048;
constexpr int GB_OFF = GA_OFF + 256;
constexpr int ONES_OFF = GB_OFF + 256;
constexpr int RED_OFF = TAB2_OFF;
constexpr int SCHED_OFF = ONES_OFF + 384;
constexpr int MISC_OFF = SCHED_OFF + 58 * 16;
constexpr int BAR_OFF = MISC_OFF + 16;
constexpr int B_FULL = 0, B_HALO = 11, B_TAB2 = 15, B_PUB = 16, B_HLD = 18, B_HRT = 22;
constexpr int B_EMPTY = 24, B_KVW = 35, B_GO = 36, B_DONE = 37, B_XF = 38, NBAR = 40;
constexpr int SMEM_BYTES = BAR_OFF + NBAR * 8;

constexpr int NB1 = 12;
constexpr uint32_t UNITS0 = 0x2210, UNITS1 = 0x776354;
constexpr int GSLP = 700;
constexpr int PUBGAP = 250;
constexpr int SPIN_LIMIT = 1 << 21;
#define DIE() asm volatile("st.global.u32 [%0], %1;" ::"l"(0ull), "r"(0) : "memory")

__device__ const uint4 c_sched[64] = {
    {512u | 0u << 16, 64u | 0u << 8 | 4095u << 16, 512u | 0u << 16, 0u | 1u << 4 | 1u << 5 | (0) << 8 | 1u << 16 | 1u << 24},
    {512u | 64u << 16, 64u | 0u << 8 | 4095u << 16, 512u | 0u << 16, 1u | 1u << 4 | 1u << 5 | (0) << 8 | 1u << 16 | 1u << 24},
    {512u | 128u << 16, 64u | 0u << 8 | 4095u << 16, 512u | 0u << 16, 2u | 1u << 4 | 1u << 5 | (0) << 8 | 1u << 16 | 1u << 24},
    {512u | 192u << 16, 64u | 0u << 8 | 4095u << 16, 512u | 0u << 16, 3u | 1u << 4 | 1u << 5 | (B_GO) << 8 | 1u << 16 | 1u << 24},
    {512u | 256u << 16, 64u | 0u << 8 | 4095u << 16, 512u | 0u << 16, 4u | 1u << 4 | 1u << 5 | (0) << 8 | 1u << 16 | 1u << 24},
    {512u | 320u << 16, 64u | 0u << 8 | 4095u << 16, 512u | 0u << 16, 5u | 1u << 4 | 1u << 5 | (0) << 8 | 1u << 16 | 1u << 24},
    {512u | 384u << 16, 64u | 0u << 8 | 4095u << 16, 512u | 0u << 16, 6u | 1u << 4 | 1u << 5 | (0) << 8 | 1u << 16 | 1u << 24},
    {512u | 448u << 16, 64u | 0u << 8 | 4095u << 16, 512u | 0u << 16, 7u | 1u << 4 | 1u << 5 | (0) << 8 | 1u << 16 | 1u << 24},
    {0u | 0u << 16, 64u | 0u << 8 | 4095u << 16, 0u | 64u << 16, 8u | 1u << 4 | 1u << 5 | (0) << 8 | 1u << 16 | 1u << 24},
    {0u | 128u << 16, 64u | 0u << 8 | 4095u << 16, 0u | 64u << 16, 9u | 1u << 4 | 1u << 5 | (0) << 8 | 1u << 16 | 1u << 24},
    {0u | 256u << 16, 64u | 0u << 8 | 4095u << 16, 0u | 64u << 16, 10u | 1u << 4 | 1u << 5 | (0) << 8 | 1u << 16 | 1u << 24},
    {0u | 384u << 16, 64u | 0u << 8 | 4095u << 16, 0u | 64u << 16, 0u | 1u << 4 | 0u << 5 | (0) << 8 | 1u << 16 | 1u << 24},
    {0u | 0u << 16, 0u | 0u << 8 | 4095u << 16, 0u | 0u << 16, 1u | 0u << 4 | 0u << 5 | (0) << 8 | 0u << 16 | 0u << 24},
    {0u | 0u << 16, 0u | 0u << 8 | 4095u << 16, 0u | 0u << 16, 2u | 0u << 4 | 0u << 5 | (0) << 8 | 0u << 16 | 0u << 24},
    {0u | 0u << 16, 0u | 0u << 8 | 4095u << 16, 0u | 0u << 16, 3u | 0u << 4 | 0u << 5 | (0) << 8 | 0u << 16 | 0u << 24},
    {0u | 0u << 16, 0u | 0u << 8 | 4095u << 16, 0u | 0u << 16, 4u | 0u << 4 | 0u << 5 | (0) << 8 | 0u << 16 | 0u << 24},
    {0u | 0u << 16, 0u | 0u << 8 | 4095u << 16, 0u | 0u << 16, 5u | 0u << 4 | 0u << 5 | (0) << 8 | 0u << 16 | 0u << 24},
    {0u | 0u << 16, 0u | 0u << 8 | 4095u << 16, 0u | 0u << 16, 6u | 0u << 4 | 0u << 5 | (0) << 8 | 0u << 16 | 0u << 24},
    {0u | 0u << 16, 64u | 0u << 8 | 4095u << 16, 0u | 64u << 16, 7u | 1u << 4 | 0u << 5 | (B_PUB) << 8 | 2u << 16 | 2u << 24},
    {0u | 128u << 16, 64u | 0u << 8 | 4095u << 16, 0u | 64u << 16, 8u | 1u << 4 | 0u << 5 | (0) << 8 | 2u << 16 | 2u << 24},
    {0u | 256u << 16, 64u | 0u << 8 | 4095u << 16, 0u | 64u << 16, 9u | 1u << 4 | 0u << 5 | (B_PUB) << 8 | 2u << 16 | 2u << 24},
    {0u | 384u << 16, 64u | 0u << 8 | 4095u << 16, 0u | 64u << 16, 10u | 1u << 4 | 0u << 5 | (0) << 8 | 2u << 16 | 2u << 24},
    {0u | 0u << 16, 176u | 0u << 8 | 4095u << 16, 0u | 0u << 16, 0u | 1u << 4 | 1u << 5 | (0) << 8 | 3u << 16 | 4u << 24},
    {0u | 64u << 16, 176u | 0u << 8 | 4095u << 16, 0u | 0u << 16, 1u | 1u << 4 | 1u << 5 | (0) << 8 | 3u << 16 | 4u << 24},
    {0u | 128u << 16, 176u | 0u << 8 | 4095u << 16, 0u | 0u << 16, 2u | 1u << 4 | 1u << 5 | (0) << 8 | 3u << 16 | 4u << 24},
    {0u | 192u << 16, 176u | 0u << 8 | 4095u << 16, 0u | 0u << 16, 3u | 1u << 4 | 1u << 5 | (0) << 8 | 3u << 16 | 4u << 24},
    {0u | 256u << 16, 176u | 0u << 8 | 4095u << 16, 0u | 0u << 16, 4u | 1u << 4 | 1u << 5 | (0) << 8 | 3u << 16 | 4u << 24},
    {0u | 320u << 16, 176u | 0u << 8 | 4095u << 16, 0u | 0u << 16, 5u | 1u << 4 | 1u << 5 | (0) << 8 | 3u << 16 | 4u << 24},
    {0u | 384u << 16, 176u | 0u << 8 | 4095u << 16, 0u | 0u << 16, 6u | 1u << 4 | 1u << 5 | (0) << 8 | 3u << 16 | 4u << 24},
    {0u | 448u << 16, 176u | 0u << 8 | 4095u << 16, 0u | 0u << 16, 7u | 1u << 4 | 1u << 5 | (0) << 8 | 3u << 16 | 4u << 24},
    {64u | 0u << 16, 176u | 0u << 8 | 4095u << 16, 0u | 0u << 16, 8u | 1u << 4 | 1u << 5 | (0) << 8 | 3u << 16 | 4u << 24},
    {64u | 64u << 16, 176u | 0u << 8 | 4095u << 16, 0u | 0u << 16, 9u | 1u << 4 | 1u << 5 | (0) << 8 | 3u << 16 | 4u << 24},
    {64u | 128u << 16, 176u | 0u << 8 | 4095u << 16, 0u | 0u << 16, 10u | 1u << 4 | 1u << 5 | (0) << 8 | 3u << 16 | 4u << 24},
    {64u | 192u << 16, 176u | 0u << 8 | 4095u << 16, 0u | 0u << 16, 0u | 1u << 4 | 0u << 5 | (0) << 8 | 3u << 16 | 4u << 24},
    {64u | 256u << 16, 176u | 0u << 8 | 4095u << 16, 0u | 0u << 16, 1u | 1u << 4 | 0u << 5 | (0) << 8 | 3u << 16 | 4u << 24},
    {64u | 320u << 16, 176u | 0u << 8 | 4095u << 16, 0u | 0u << 16, 2u | 1u << 4 | 0u << 5 | (0) << 8 | 3u << 16 | 4u << 24},
    {64u | 384u << 16, 176u | 0u << 8 | 4095u << 16, 0u | 0u << 16, 3u | 1u << 4 | 0u << 5 | (0) << 8 | 3u << 16 | 4u << 24},
    {64u | 448u << 16, 176u | 0u << 8 | 4095u << 16, 0u | 0u << 16, 4u | 1u << 4 | 0u << 5 | (0) << 8 | 3u << 16 | 4u << 24},
    {128u | 0u << 16, 176u | 0u << 8 | 4095u << 16, 0u | 0u << 16, 5u | 1u << 4 | 0u << 5 | (0) << 8 | 3u << 16 | 4u << 24},
    {128u | 64u << 16, 176u | 0u << 8 | 4095u << 16, 0u | 0u << 16, 6u | 1u << 4 | 0u << 5 | (0) << 8 | 3u << 16 | 4u << 24},
    {128u | 128u << 16, 176u | 0u << 8 | 4095u << 16, 0u | 0u << 16, 7u | 1u << 4 | 0u << 5 | (0) << 8 | 3u << 16 | 4u << 24},
    {128u | 192u << 16, 176u | 0u << 8 | 4095u << 16, 0u | 0u << 16, 8u | 1u << 4 | 0u << 5 | (0) << 8 | 3u << 16 | 4u << 24},
    {128u | 256u << 16, 176u | 0u << 8 | 4095u << 16, 0u | 0u << 16, 9u | 1u << 4 | 0u << 5 | (0) << 8 | 3u << 16 | 4u << 24},
    {128u | 320u << 16, 176u | 0u << 8 | 4095u << 16, 0u | 0u << 16, 10u | 1u << 4 | 0u << 5 | (0) << 8 | 3u << 16 | 4u << 24},
    {128u | 384u << 16, 176u | 0u << 8 | 4095u << 16, 0u | 0u << 16, 0u | 1u << 4 | 1u << 5 | (0) << 8 | 3u << 16 | 4u << 24},
    {128u | 448u << 16, 176u | 0u << 8 | 4095u << 16, 0u | 0u << 16, 1u | 1u << 4 | 1u << 5 | (0) << 8 | 3u << 16 | 4u << 24},
    {0u | 0u << 16, 64u | 176u << 8 | 511u << 16, 0u | 176u << 16, 2u | 1u << 4 | 1u << 5 | (0) << 8 | 5u << 16 | 5u << 24},
    {0u | 64u << 16, 64u | 176u << 8 | 511u << 16, 0u | 176u << 16, 3u | 1u << 4 | 1u << 5 | (0) << 8 | 5u << 16 | 5u << 24},
    {128u | 0u << 16, 64u | 176u << 8 | 511u << 16, 0u | 176u << 16, 4u | 1u << 4 | 1u << 5 | (0) << 8 | 5u << 16 | 5u << 24},
    {128u | 64u << 16, 64u | 176u << 8 | 511u << 16, 0u | 176u << 16, 5u | 1u << 4 | 1u << 5 | (0) << 8 | 5u << 16 | 5u << 24},
    {128u | 128u << 16, 64u | 176u << 8 | 511u << 16, 0u | 176u << 16, 6u | 1u << 4 | 1u << 5 | (0) << 8 | 5u << 16 | 5u << 24},
    {256u | 0u << 16, 64u | 176u << 8 | 511u << 16, 0u | 176u << 16, 7u | 1u << 4 | 1u << 5 | (0) << 8 | 5u << 16 | 5u << 24},
    {256u | 64u << 16, 64u | 176u << 8 | 511u << 16, 0u | 176u << 16, 8u | 1u << 4 | 1u << 5 | (0) << 8 | 5u << 16 | 5u << 24},
    {256u | 128u << 16, 64u | 176u << 8 | 511u << 16, 0u | 176u << 16, 9u | 1u << 4 | 1u << 5 | (0) << 8 | 5u << 16 | 5u << 24},
    {384u | 0u << 16, 64u | 176u << 8 | 511u << 16, 0u | 176u << 16, 10u | 1u << 4 | 1u << 5 | (0) << 8 | 5u << 16 | 5u << 24},
    {384u | 64u << 16, 64u | 176u << 8 | 511u << 16, 0u | 176u << 16, 0u | 1u << 4 | 0u << 5 | (0) << 8 | 5u << 16 | 5u << 24},
    {384u | 128u << 16, 64u | 176u << 8 | 511u << 16, 0u | 176u << 16, 1u | 1u << 4 | 0u << 5 | (0) << 8 | 5u << 16 | 5u << 24},
    {0u | 128u << 16, 64u | 176u << 8 | 511u << 16, 0u | 176u << 16, 2u | 1u << 4 | 0u << 5 | (0) << 8 | 5u << 16 | 5u << 24},
};

__device__ uint4 g_kv[16 * 8 * 2048];
constexpr int X_O = 0, X_X1 = 32, X_HH = 64, X_PT = 160, X_XR = 256, X_ST = 288, X_ROWS = 290;
__device__ uint4 g_x[16 * 8 * X_ROWS * 32];
__device__ uint4 g_m1[512];
__device__ uint4 g_m2[512];
__device__ uint4 g_rs[2048];
__device__ unsigned g_cnt;

__device__ __forceinline__ uint32_t s2u(const void* p) { return (uint32_t)__cvta_generic_to_shared(p); }
__device__ __forceinline__ bool elect() {
    uint32_t p;
    asm volatile("{\n.reg .pred p;\nelect.sync _|p, 0xffffffff;\nselp.u32 %0, 1, 0, p;\n}" : "=r"(p));
    return p;
}
__device__ __forceinline__ void mbar_init(uint32_t b, int c) {
    asm volatile("mbarrier.init.shared::cta.b64 [%0], %1;" ::"r"(b), "r"(c) : "memory");
}
__device__ __forceinline__ void mbar_expect(uint32_t b, uint32_t bytes) {
    asm volatile("mbarrier.arrive.expect_tx.shared::cta.b64 _, [%0], %1;" ::"r"(b), "r"(bytes) : "memory");
}
__device__ __forceinline__ void mbar_arrive(uint32_t b) {
    asm volatile("mbarrier.arrive.shared::cta.b64 _, [%0];" ::"r"(b) : "memory");
}
__device__ __forceinline__ void mbar_arrive1(uint32_t b) {
    asm volatile("{\n.reg .pred p;\nelect.sync _|p, 0xffffffff;\n@p mbarrier.arrive.shared::cta.b64 _, [%0];\n}" ::"r"(b) : "memory");
}
__device__ __forceinline__ void mbar_arrive_lt(uint32_t b, int a, int n) {
    asm volatile("{\n.reg .pred p;\nsetp.lt.s32 p, %1, %2;\n@p mbarrier.arrive.shared::cta.b64 _, [%0];\n}" ::"r"(b), "r"(a), "r"(n) : "memory");
}
__device__ __forceinline__ void mbar_wait(uint32_t b, uint32_t ph) {
    asm volatile("{\n.reg .pred p;\nLOOP_%=:\nmbarrier.try_wait.parity.shared::cta.b64 p, [%0], %1;\n@!p bra LOOP_%=;\n}"
                 ::"r"(b), "r"(ph) : "memory");
}
__device__ __forceinline__ void mbar_wait_b(uint32_t b, uint32_t ph) {
    asm volatile(
        "{\n.reg .pred p;\n.reg .u32 n;\n"
        "mov.u32 n, 0;\n"
        "LOOP_%=:\n"
        "mbarrier.try_wait.parity.shared::cta.b64 p, [%0], %1;\n"
        "@p bra DONE_%=;\n"
        "add.u32 n, n, 1;\n"
        "setp.lt.u32 p, n, %2;\n"
        "@p bra LOOP_%=;\n"
        "st.global.u32 [%3], n;\n"
        "DONE_%=:\n}" ::"r"(b), "r"(ph), "n"(SPIN_LIMIT), "l"(0ull) : "memory");
}
__device__ __forceinline__ void bar_sync(int id, int n) { asm volatile("bar.sync %0, %1;" ::"r"(id), "r"(n) : "memory"); }
__device__ __forceinline__ void bar_arrive(int id, int n) { asm volatile("bar.arrive %0, %1;" ::"r"(id), "r"(n) : "memory"); }
__device__ __forceinline__ void bar_sync_if(int c, int id, int n) {
    asm volatile("{\n.reg .pred p;\nsetp.ne.u32 p, %0, 0;\n@p bar.sync %1, %2;\n}" ::"r"(c), "r"(id), "r"(n) : "memory");
}
__device__ __forceinline__ void bar_arrive_if(int c, int id, int n) {
    asm volatile("{\n.reg .pred p;\nsetp.ne.u32 p, %0, 0;\n@p bar.arrive %1, %2;\n}" ::"r"(c), "r"(id), "r"(n) : "memory");
}
__device__ __forceinline__ void fence_async_smem() { asm volatile("fence.proxy.async.shared::cta;" ::: "memory"); }

__device__ __forceinline__ void tma2d(uint32_t dst, const CUtensorMap* m, int c0, int c1, uint32_t bar) {
    asm volatile("cp.async.bulk.tensor.2d.shared::cluster.global.mbarrier::complete_tx::bytes [%0], [%1, {%3, %4}], [%2];"
                 ::"r"(dst), "l"(m), "r"(bar), "r"(c0), "r"(c1) : "memory");
}
__device__ __forceinline__ void bulk_g2s(uint32_t dst, const void* src, uint32_t bytes, uint32_t bar) {
    asm volatile("cp.async.bulk.shared::cluster.global.mbarrier::complete_tx::bytes [%0], [%1], %2, [%3];"
                 ::"r"(dst), "l"(src), "r"(bytes), "r"(bar) : "memory");
}
__device__ __forceinline__ void bulk_s2g(void* dst, uint32_t src, uint32_t bytes) {
    asm volatile("cp.async.bulk.global.shared::cta.bulk_group [%0], [%1], %2;" ::"l"(dst), "r"(src), "r"(bytes) : "memory");
}
__device__ __forceinline__ void prefetch_l2(const void* p, uint32_t bytes) {
    asm volatile("cp.async.bulk.prefetch.L2.global [%0], %1;" ::"l"(p), "r"(bytes) : "memory");
}
__device__ __forceinline__ uint4 ldg_nc(const void* p) {
    uint4 v;
    asm volatile("ld.global.nc.v4.u32 {%0,%1,%2,%3}, [%4];" : "=r"(v.x), "=r"(v.y), "=r"(v.z), "=r"(v.w) : "l"(p));
    return v;
}
__device__ __forceinline__ unsigned ld_u32(const unsigned* p) {
    unsigned v;
    asm volatile("ld.relaxed.gpu.global.u32 %0, [%1];" : "=r"(v) : "l"(p) : "memory");
    return v;
}
__device__ __forceinline__ uint4 ld_rlx(const void* p) {
    uint4 v;
    asm volatile("ld.relaxed.gpu.global.v4.u32 {%0,%1,%2,%3}, [%4];" : "=r"(v.x), "=r"(v.y), "=r"(v.z), "=r"(v.w) : "l"(p) : "memory");
    return v;
}
__device__ __forceinline__ void st_rlx(void* p, uint32_t x, uint32_t y, uint32_t z, uint32_t w) {
    asm volatile("st.relaxed.gpu.global.v4.u32 [%0], {%1,%2,%3,%4};" ::"l"(p), "r"(x), "r"(y), "r"(z), "r"(w) : "memory");
}
__device__ __forceinline__ uint32_t tagw(uint32_t x, uint32_t par) {
    uint32_t d;
    asm("lop3.b32 %0, %1, 0xfffffffe, %2, 0xea;" : "=r"(d) : "r"(x), "r"(par));
    return d;
}
template <int N>
__device__ __forceinline__ bool stale(const uint4* v, uint32_t par) {
    uint32_t bad = 0;
#pragma unroll
    for (int i = 0; i < N; ++i) asm("lop3.b32 %0, %1, %2, %0, 0xbe;" : "+r"(bad) : "r"(v[i].x), "r"(par));
    return __any_sync(~0u, bad & 1u);
}
template <int N, class F>
__device__ __forceinline__ void poll(uint4* v, const uint4* p, F off, uint32_t par) {
#pragma unroll 1
    do {
#pragma unroll
        for (int i = 0; i < N; ++i) v[i] = ld_rlx(p + off(i));
    } while (stale<N>(v, par));
}
template <int N, class F>
__device__ __forceinline__ void validate(uint4* v, const uint4* p, F off, uint32_t par) {
    if (__builtin_expect(stale<N>(v, par), 0)) poll<N>(v, p, off, par);
}
__device__ __forceinline__ uint4 lds128(uint32_t a) {
    uint4 v;
    asm volatile("ld.shared.v4.u32 {%0,%1,%2,%3}, [%4];" : "=r"(v.x), "=r"(v.y), "=r"(v.z), "=r"(v.w) : "r"(a) : "memory");
    return v;
}
__device__ __forceinline__ uint32_t lds32(uint32_t a) {
    uint32_t v;
    asm volatile("ld.shared.u32 %0, [%1];" : "=r"(v) : "r"(a) : "memory");
    return v;
}
__device__ __forceinline__ void sts128(uint32_t a, uint32_t x, uint32_t y, uint32_t z, uint32_t w) {
    asm volatile("st.shared.v4.u32 [%0], {%1,%2,%3,%4};" ::"r"(a), "r"(x), "r"(y), "r"(z), "r"(w) : "memory");
}
__device__ __forceinline__ void stsm4(uint32_t a, uint32_t x, uint32_t y, uint32_t z, uint32_t w) {
    asm volatile("stmatrix.sync.aligned.m8n8.x4.shared.b16 [%0], {%1,%2,%3,%4};" ::"r"(a), "r"(x), "r"(y), "r"(z), "r"(w) : "memory");
}
__device__ __forceinline__ uint4 ldsm4(uint32_t a) {
    uint4 v;
    asm volatile("ldmatrix.sync.aligned.m8n8.x4.shared.b16 {%0,%1,%2,%3}, [%4];" : "=r"(v.x), "=r"(v.y), "=r"(v.z), "=r"(v.w) : "r"(a) : "memory");
    return v;
}
__device__ __forceinline__ uint4 ldsm4t(uint32_t a) {
    uint4 v;
    asm volatile("ldmatrix.sync.aligned.m8n8.x4.trans.shared.b16 {%0,%1,%2,%3}, [%4];" : "=r"(v.x), "=r"(v.y), "=r"(v.z), "=r"(v.w) : "r"(a) : "memory");
    return v;
}
template <int ACC, int NT = 2>
__device__ __forceinline__ void mma2(float* d, const uint4& a, const uint4& b) {
#pragma unroll
    for (int i = 0; i < NT; ++i)
        asm("mma.sync.aligned.m16n8k16.row.col.f32.bf16.bf16.f32 {%0,%1,%2,%3}, {%4,%5,%6,%7}, {%8,%9}, {%10,%11,%12,%13};"
            : "=f"(d[4 * i]), "=f"(d[4 * i + 1]), "=f"(d[4 * i + 2]), "=f"(d[4 * i + 3])
            : "r"(a.x), "r"(a.y), "r"(a.z), "r"(a.w), "r"(i ? b.z : b.x), "r"(i ? b.w : b.y), "f"(ACC ? d[4 * i] : 0.f),
              "f"(ACC ? d[4 * i + 1] : 0.f), "f"(ACC ? d[4 * i + 2] : 0.f), "f"(ACC ? d[4 * i + 3] : 0.f));
}
__device__ __forceinline__ uint32_t pack2(float lo, float hi) {
    uint32_t d;
    asm("cvt.rn.bf16x2.f32 %0, %1, %2;" : "=r"(d) : "f"(hi), "f"(lo));
    return d;
}
__device__ __forceinline__ uint4 pack8(const float* a) {
    return make_uint4(pack2(a[0], a[1]), pack2(a[2], a[3]), pack2(a[4], a[5]), pack2(a[6], a[7]));
}
__device__ __forceinline__ float bf_lo(uint32_t x) { return __uint_as_float(x << 16); }
__device__ __forceinline__ float bf_hi(uint32_t x) { return __uint_as_float(x & 0xffff0000u); }
__device__ __forceinline__ float u2f(uint32_t v) { return __uint_as_float(v); }
__device__ __forceinline__ uint32_t f2u(float v) { return __float_as_uint(v); }
__device__ __forceinline__ uint32_t hfma2(uint32_t a, uint32_t b, uint32_t c) {
    uint32_t d;
    asm("fma.rn.bf16x2 %0, %1, %2, %3;" : "=r"(d) : "r"(a), "r"(b), "r"(c));
    return d;
}
__device__ __forceinline__ uint32_t hmul2(uint32_t a, uint32_t b) {
    uint32_t d;
    asm("mul.rn.bf16x2 %0, %1, %2;" : "=r"(d) : "r"(a), "r"(b));
    return d;
}
__device__ __forceinline__ uint4 gate8(const float* a, const float* b) {
    const uint4 u = pack8(a), v = pack8(b);
    return make_uint4(hmul2(u.x, v.x), hmul2(u.y, v.y), hmul2(u.z, v.z), hmul2(u.w, v.w));
}
__device__ __forceinline__ float ex2f(float x) {
    float y;
    asm("ex2.approx.ftz.f32 %0, %1;" : "=f"(y) : "f"(x));
    return y;
}
__device__ __forceinline__ float rcpf(float x) {
    float y;
    asm("rcp.approx.ftz.f32 %0, %1;" : "=f"(y) : "f"(x));
    return y;
}
__device__ __forceinline__ float sqrtaf(float x) {
    float y;
    asm("sqrt.approx.ftz.f32 %0, %1;" : "=f"(y) : "f"(x));
    return y;
}
#define WG_FENCE() asm volatile("wgmma.fence.sync.aligned;" ::: "memory")
#define WG_COMMIT() asm volatile("wgmma.commit_group.sync.aligned;" ::: "memory")
#define WG_WAIT(n) asm volatile("wgmma.wait_group.sync.aligned %0;" ::"n"(n) : "memory")
template <int N>
__device__ __forceinline__ void pin(float* d) {
#pragma unroll
    for (int i = 0; i < N; ++i) asm volatile("" : "+f"(d[i])::"memory");
}

__device__ __forceinline__ uint64_t bdesc(uint32_t addr) {
    return (uint64_t)((addr >> 4) | (512u << 16)) | ((uint64_t)(64u | (1u << 30)) << 32);
}
__device__ __forceinline__ uint64_t cdesc(uint32_t addr, uint32_t lbo, uint32_t sbo) {
    return (uint64_t)((addr >> 4) | ((lbo >> 4) << 16)) | ((uint64_t)(sbo >> 4) << 32);
}
template <int SC>
__device__ __forceinline__ void wgmma128(float* d, const uint4& a, uint64_t db) {
    asm volatile("wgmma.mma_async.sync.aligned.m64n128k16.f32.bf16.bf16 {%0,%1,%2,%3,%4,%5,%6,%7,%8,%9,%10,%11,%12,%13,%14,%15,%16,%17,%18,%19,%20,%21,%22,%23,%24,%25,%26,%27,%28,%29,%30,%31,%32,%33,%34,%35,%36,%37,%38,%39,%40,%41,%42,%43,%44,%45,%46,%47,%48,%49,%50,%51,%52,%53,%54,%55,%56,%57,%58,%59,%60,%61,%62,%63}, "
                 "{%64,%65,%66,%67}, %68, %69, 1, 1, 1;"
                 : "+f"(d[0]), "+f"(d[1]), "+f"(d[2]), "+f"(d[3]), "+f"(d[4]), "+f"(d[5]), "+f"(d[6]), "+f"(d[7]), "+f"(d[8]), "+f"(d[9]), "+f"(d[10]), "+f"(d[11]), "+f"(d[12]), "+f"(d[13]), "+f"(d[14]), "+f"(d[15]), "+f"(d[16]), "+f"(d[17]), "+f"(d[18]), "+f"(d[19]), "+f"(d[20]), "+f"(d[21]), "+f"(d[22]), "+f"(d[23]), "+f"(d[24]), "+f"(d[25]), "+f"(d[26]), "+f"(d[27]), "+f"(d[28]), "+f"(d[29]), "+f"(d[30]), "+f"(d[31]), "+f"(d[32]), "+f"(d[33]), "+f"(d[34]), "+f"(d[35]), "+f"(d[36]), "+f"(d[37]), "+f"(d[38]), "+f"(d[39]), "+f"(d[40]), "+f"(d[41]), "+f"(d[42]), "+f"(d[43]), "+f"(d[44]), "+f"(d[45]), "+f"(d[46]), "+f"(d[47]), "+f"(d[48]), "+f"(d[49]), "+f"(d[50]), "+f"(d[51]), "+f"(d[52]), "+f"(d[53]), "+f"(d[54]), "+f"(d[55]), "+f"(d[56]), "+f"(d[57]), "+f"(d[58]), "+f"(d[59]), "+f"(d[60]), "+f"(d[61]), "+f"(d[62]), "+f"(d[63])
                 : "r"(a.x), "r"(a.y), "r"(a.z), "r"(a.w), "l"(db), "n"(SC));
}
template <int SC>
__device__ __forceinline__ void wgmma64(float* d, const uint4& a, uint64_t db) {
    asm volatile("wgmma.mma_async.sync.aligned.m64n64k16.f32.bf16.bf16 {%0,%1,%2,%3,%4,%5,%6,%7,%8,%9,%10,%11,%12,%13,%14,%15,%16,%17,%18,%19,%20,%21,%22,%23,%24,%25,%26,%27,%28,%29,%30,%31}, "
                 "{%32,%33,%34,%35}, %36, %37, 1, 1, 1;"
                 : "+f"(d[0]), "+f"(d[1]), "+f"(d[2]), "+f"(d[3]), "+f"(d[4]), "+f"(d[5]), "+f"(d[6]), "+f"(d[7]), "+f"(d[8]), "+f"(d[9]), "+f"(d[10]), "+f"(d[11]), "+f"(d[12]), "+f"(d[13]), "+f"(d[14]), "+f"(d[15]), "+f"(d[16]), "+f"(d[17]), "+f"(d[18]), "+f"(d[19]), "+f"(d[20]), "+f"(d[21]), "+f"(d[22]), "+f"(d[23]), "+f"(d[24]), "+f"(d[25]), "+f"(d[26]), "+f"(d[27]), "+f"(d[28]), "+f"(d[29]), "+f"(d[30]), "+f"(d[31])
                 : "r"(a.x), "r"(a.y), "r"(a.z), "r"(a.w), "l"(db), "n"(SC));
}
template <int SC>
__device__ __forceinline__ void wgmma48(float* d, const uint4& a, uint64_t db) {
    asm volatile("wgmma.mma_async.sync.aligned.m64n48k16.f32.bf16.bf16 {%0,%1,%2,%3,%4,%5,%6,%7,%8,%9,%10,%11,%12,%13,%14,%15,%16,%17,%18,%19,%20,%21,%22,%23}, "
                 "{%24,%25,%26,%27}, %28, %29, 1, 1, 1;"
                 : "+f"(d[0]), "+f"(d[1]), "+f"(d[2]), "+f"(d[3]), "+f"(d[4]), "+f"(d[5]), "+f"(d[6]), "+f"(d[7]), "+f"(d[8]), "+f"(d[9]), "+f"(d[10]), "+f"(d[11]), "+f"(d[12]), "+f"(d[13]), "+f"(d[14]), "+f"(d[15]), "+f"(d[16]), "+f"(d[17]), "+f"(d[18]), "+f"(d[19]), "+f"(d[20]), "+f"(d[21]), "+f"(d[22]), "+f"(d[23])
                 : "r"(a.x), "r"(a.y), "r"(a.z), "r"(a.w), "l"(db), "n"(SC));
}
template <int SC>
__device__ __forceinline__ void wgmma16(float* d, const uint4& a, uint64_t db) {
    asm volatile("wgmma.mma_async.sync.aligned.m64n16k16.f32.bf16.bf16 {%0,%1,%2,%3,%4,%5,%6,%7}, "
                 "{%8,%9,%10,%11}, %12, %13, 1, 1, 1;"
                 : "+f"(d[0]), "+f"(d[1]), "+f"(d[2]), "+f"(d[3]), "+f"(d[4]), "+f"(d[5]), "+f"(d[6]), "+f"(d[7])
                 : "r"(a.x), "r"(a.y), "r"(a.z), "r"(a.w), "l"(db), "n"(SC));
}

struct LnC { uint32_t rs0, nm0, rs1, nm1; };
__device__ __forceinline__ void ln_mod(uint4& a, uint4 cs, const LnC& c) {
    a.x = hfma2(hfma2(a.x, c.rs0, c.nm0), cs.x, cs.z);
    a.y = hfma2(hfma2(a.y, c.rs1, c.nm1), cs.x, cs.z);
    a.z = hfma2(hfma2(a.z, c.rs0, c.nm0), cs.y, cs.w);
    a.w = hfma2(hfma2(a.w, c.rs1, c.nm1), cs.y, cs.w);
}
__device__ __forceinline__ float rbf(float v) { return bf_lo(pack2(v, v)); }
__device__ __forceinline__ float silu_bf(float c) {
    float s = c * rcpf(1.0f + ex2f(c * -1.4426950408889634f));
    return rbf(s);
}
__device__ __forceinline__ void fma8(float* a, float s, uint4 w) {
    a[0] = fmaf(s, bf_lo(w.x), a[0]); a[1] = fmaf(s, bf_hi(w.x), a[1]);
    a[2] = fmaf(s, bf_lo(w.y), a[2]); a[3] = fmaf(s, bf_hi(w.y), a[3]);
    a[4] = fmaf(s, bf_lo(w.z), a[4]); a[5] = fmaf(s, bf_hi(w.z), a[5]);
    a[6] = fmaf(s, bf_lo(w.w), a[6]); a[7] = fmaf(s, bf_hi(w.w), a[7]);
}
__device__ __forceinline__ void red8(float* a, int lane) {
    const bool u16 = lane & 16, u8 = lane & 8, u4 = lane & 4;
#pragma unroll
    for (int k = 0; k < 4; ++k) {
        float keep = u16 ? a[k + 4] : a[k], send = u16 ? a[k] : a[k + 4];
        a[k] = keep + __shfl_xor_sync(~0u, send, 16);
    }
#pragma unroll
    for (int k = 0; k < 2; ++k) {
        float keep = u8 ? a[k + 2] : a[k], send = u8 ? a[k] : a[k + 2];
        a[k] = keep + __shfl_xor_sync(~0u, send, 8);
    }
    float keep = u4 ? a[1] : a[0], send = u4 ? a[0] : a[1];
    a[0] = keep + __shfl_xor_sync(~0u, send, 4);
    a[0] += __shfl_xor_sync(~0u, a[0], 2);
}
__device__ __forceinline__ void sumsq(uint32_t v, float& s, float& q) {
    const float a = bf_lo(v), b = bf_hi(v);
    s += a + b;
    q = fmaf(a, a, fmaf(b, b, q));
}
__device__ __forceinline__ void row_stats(float s, float q, uint32_t& rs, uint32_t& nm) {
    const float mean = s * (1.f / 512.f);
    const float var = rbf(rbf(fmaxf(fmaf(-mean, mean, q * (1.f / 512.f)), 0.f)) + 1e-5f);
    const float inv = rcpf(rbf(sqrtaf(var)));
    rs = pack2(inv, inv);
    const float m = -rbf(mean) * bf_lo(rs);
    nm = pack2(m, m);
}
__device__ __forceinline__ uint32_t one_plus(uint32_t v) { return pack2(1.0f + bf_lo(v), 1.0f + bf_hi(v)); }
__device__ __forceinline__ uint4 exp_pack(const float* s) {
    return make_uint4(pack2(ex2f(s[0]), ex2f(s[1])), pack2(ex2f(s[2]), ex2f(s[3])), pack2(ex2f(s[4]), ex2f(s[5])),
                      pack2(ex2f(s[6]), ex2f(s[7])));
}
template <int NB>
__device__ __forceinline__ void maxb(const float* s, float& m0, float& m1) {
#pragma unroll
    for (int i = 0; i < NB; ++i) {
        m0 = fmaxf(m0, fmaxf(fmaxf(s[8 * i], s[8 * i + 1]), fmaxf(s[8 * i + 4], s[8 * i + 5])));
        m1 = fmaxf(m1, fmaxf(fmaxf(s[8 * i + 2], s[8 * i + 3]), fmaxf(s[8 * i + 6], s[8 * i + 7])));
    }
}

struct Maps { CUtensorMap m[6]; };

__global__ void __launch_bounds__(384, 1)
fused_kernel(const __nv_bfloat16* __restrict__ x, const __nv_bfloat16* __restrict__ wqkv, const __nv_bfloat16* __restrict__ wo,
             const __nv_bfloat16* __restrict__ wg, const __nv_bfloat16* __restrict__ wu, const __nv_bfloat16* __restrict__ wd,
             const __nv_bfloat16* __restrict__ cvec, const __nv_bfloat16* __restrict__ wmod, __nv_bfloat16* __restrict__ out,
             const __grid_constant__ Maps tm) {
    extern __shared__ __align__(1024) unsigned char smem[];
    constexpr uint32_t sb = 1024;
    constexpr uint32_t bars = sb + BAR_OFF;
    const int bid = blockIdx.x;
    const int j = bid >> 3, r = bid & 7;
    const int lane = threadIdx.x & 31;
    const int warp = __shfl_sync(~0u, threadIdx.x >> 5, 0);
#define RELEASE(s0, n) do { _Pragma("unroll") for (int q_ = 0; q_ < (n); ++q_) mbar_arrive1(bars + 8 * (B_EMPTY + (s0) + q_)); } while (0)

    if (warp == 8) {
        if (elect()) {
            mbar_init(bars + 8 * B_XF, 1);
            mbar_init(bars + 8 * B_XF + 8, 1);
            mbar_expect(bars + 8 * B_XF, 4 * STAGE_BYTES);
            mbar_expect(bars + 8 * B_XF + 8, 4 * STAGE_BYTES);
#pragma unroll 1
            for (int n = 0; n < 8; ++n) tma2d(sb + (3 + n) * STAGE_BYTES, &tm.m[0], 64 * n, 128 * j, bars + 8 * (B_XF + (n >> 2)));
            if (s2u(smem) != sb) DIE();
#pragma unroll 1
            for (int i = 0; i < B_XF; i += 2) { mbar_init(bars + 8 * i, i < B_EMPTY ? 1 : 8); mbar_init(bars + 8 * i + 8, i < B_EMPTY ? 1 : 8); }
        }
        __syncwarp();
        bar_arrive(0, 288);
    }
    volatile unsigned* s_epoch = (volatile unsigned*)(smem + MISC_OFF);

    if (warp < 8) {
        const int w = warp, g = lane >> 2, t = lane & 3;
        const int row0 = 128 * j + 16 * w + g;
        uint4 A[32];
        LnC ln;
#define DB0(z) bdesc(sb + (z) * 16)
        uint32_t par;
        uint4* xb = g_x + (size_t)(j * 8 + w) * (X_ROWS * 32) + lane;
        asm volatile("mov.b64 %0, %0;" : "+l"(xb));
#define XROW(row) (xb + (row) * 32)
#define XR2(rt, row) (xb + (rt) * 32 + (row) * 32)
        {
            const unsigned epoch = (ld_u32(&g_cnt) >> 7) + 1;
            const int mrow = 256 * (bid & 1) + (threadIdx.x >> 1) * 2;
            const __nv_bfloat16* wp = wmod + (size_t)mrow * 3072 + 16 * (bid >> 1) + 8 * (lane & 1);
            const uint4 wv0 = ldg_nc(wp), wv1 = ldg_nc(wp + 3072);
            const uint32_t cv = __ldg((const uint32_t*)(cvec + mrow));
            const int srow = 128 * j + 16 * r + 2 * w + (lane >> 4);
            uint4 xs[4];
#pragma unroll
            for (int i = 0; i < 4; ++i) xs[i] = ldg_nc((const uint4*)x + (size_t)srow * 64 + i * 16 + (lane & 15));
            if ((lane & 15) == 0) st_rlx(&g_rs[srow], ~epoch, 0, 0, 0);
            if (threadIdx.x < 4) st_rlx(&g_m1[bid * 4 + lane], ~epoch, 0, 0, 0);
            float a[8];
#pragma unroll
            for (int k = 0; k < 8; ++k) a[k] = 0.f;
            fma8(a, silu_bf(bf_lo(cv)), wv0);
            fma8(a, silu_bf(bf_hi(cv)), wv1);
            red8(a, lane);
            float* red = (float*)(smem + RED_OFF);
            if ((lane & 2) == 0) red[w * 16 + (lane & 1) * 8 + (lane >> 2)] = a[0];
            float sm = 0.f, sq = 0.f;
#pragma unroll
            for (int i = 0; i < 4; ++i) { sumsq(xs[i].x, sm, sq); sumsq(xs[i].y, sm, sq); sumsq(xs[i].z, sm, sq); sumsq(xs[i].w, sm, sq); }
#pragma unroll
            for (int o = 1; o < 16; o <<= 1) { sm += __shfl_xor_sync(~0u, sm, o); sq += __shfl_xor_sync(~0u, sq, o); }
            uint32_t rs, nm;
            row_stats(sm, sq, rs, nm);
            par = epoch & 1u;
            *s_epoch = epoch;
            bar_sync(0, 288);
            if (threadIdx.x == 64) asm volatile("red.relaxed.gpu.global.add.u32 [%0], 1;" ::"l"(&g_cnt) : "memory");
            if (w == 1 && elect()) prefetch_l2((const char*)wqkv + bid * 12288, 12288);
            if ((lane & 15) == 0) st_rlx(&g_rs[srow], par, rs, nm, 0u);
            if (w == 0) {
                float4 v = *(const float4*)(red + 4 * lane);
#pragma unroll
                for (int o = 4; o < 32; o <<= 1) {
                    v.x += __shfl_xor_sync(~0u, v.x, o); v.y += __shfl_xor_sync(~0u, v.y, o);
                    v.z += __shfl_xor_sync(~0u, v.z, o); v.w += __shfl_xor_sync(~0u, v.w, o);
                }
                if (lane < 4) st_rlx(&g_m1[bid * 4 + lane], tagw(f2u(v.x), par), f2u(v.y), f2u(v.z), f2u(v.w));
            }
            asm volatile("setmaxnreg.inc.sync.aligned.u32 232;");
            uint4 pv[4];
            const uint4* mp = &g_m1[(threadIdx.x >> 2) * 8 + t];
            {
                const uint32_t xa = sb + 3 * STAGE_BYTES + (16 * w + (lane & 15)) * 128 + (((lane >> 4) ^ lane) & 7) * 16;
#pragma unroll
                for (int i = 0; i < 8; ++i) {
                    if ((i & 3) == 0) mbar_wait(bars + 8 * (B_XF + (i >> 2)), 0);
#pragma unroll
                    for (int c = 0; c < 4; ++c) A[4 * i + c] = ldsm4((xa ^ (c * 32)) + i * STAGE_BYTES);
                }
#pragma unroll
                for (int c = 0; c < 4; ++c) xs[c] = ldsm4((xa ^ (c * 32)) + r * STAGE_BYTES);
            }
#pragma unroll 1
            do {
                pv[0] = ld_rlx(mp); pv[1] = ld_rlx(mp + 4);
                pv[2] = ld_rlx(&g_rs[row0]); pv[3] = ld_rlx(&g_rs[row0 + 8]);
            } while (stale<4>(pv, par));
            mbar_arrive1(bars + 8 * B_GO);
#pragma unroll
            for (int c = 0; c < 4; ++c) st_rlx(XR2(4 * r, X_XR + c), xs[c].x, xs[c].y, xs[c].z, xs[c].w);
            const int i = threadIdx.x & 127;
            uint32_t v0 = pack2(u2f(pv[0].x) + u2f(pv[1].x), u2f(pv[0].y) + u2f(pv[1].y));
            uint32_t v1 = pack2(u2f(pv[0].z) + u2f(pv[1].z), u2f(pv[0].w) + u2f(pv[1].w));
            if (w >= 4) { v0 = one_plus(v0); v1 = one_plus(v1); }
            uint32_t* tp = (uint32_t*)(smem + TAB1_OFF) + (i >> 2) * 16 + (i & 1) * 8 + ((i >> 1) & 1) + (w >= 4 ? 0 : 2);
            tp[0] = v0; tp[4] = v1;
            ln.rs0 = pv[2].y; ln.nm0 = pv[2].z; ln.rs1 = pv[3].y; ln.nm1 = pv[3].z;
            bar_sync(1, 256);
        }

        uint4 x1k = make_uint4(0, 0, 0, 0);
#pragma unroll 1
        for (int ph = 0; ph < 3; ++ph) {
            float acc[64];
            {
                const uint32_t tab = sb + (ph ? TAB2_OFF : TAB1_OFF) + t * 16;
                if (ph == 1) {
                    uint4 sv[2];
                    poll<2>(sv, XROW(X_ST) - lane + 16 * t + g, [](int i) { return 8 * i; }, par);
#pragma unroll
                    for (int i = 0; i < NB1; ++i) A[i] = ld_rlx(XROW(X_X1 + i));
                    float q0 = u2f(sv[0].x) + u2f(sv[1].x), s0 = u2f(sv[0].y) + u2f(sv[1].y);
                    float q1 = u2f(sv[0].z) + u2f(sv[1].z), s1 = u2f(sv[0].w) + u2f(sv[1].w);
#pragma unroll
                    for (int o = 1; o < 4; o <<= 1) {
                        s0 += __shfl_xor_sync(~0u, s0, o); q0 += __shfl_xor_sync(~0u, q0, o);
                        s1 += __shfl_xor_sync(~0u, s1, o); q1 += __shfl_xor_sync(~0u, q1, o);
                    }
                    row_stats(s0, q0, ln.rs0, ln.nm0);
                    row_stats(s1, q1, ln.rs1, ln.nm1);
                    validate<NB1>(A, XROW(X_X1), [](int i) { return 32 * i; }, par);
#pragma unroll
                    for (int i = NB1; i < 32; ++i) A[i] = ld_rlx(XROW(X_X1 + i));
                    bar_sync_if(w < 4, 4, 256);
                }
                uint4 cs[4];
#pragma unroll
                for (int c = 0; c < 4; ++c) cs[c] = lds128(tab + c * 64);
#pragma unroll
                for (int i = 0; i < 8; ++i) {
                    const int slot = ph == 2 ? (8 + i) % NSTAGE : i, prev = ph == 2 ? (6 + i) % NSTAGE : i - 2;
                    if (4 * i == NB1 && ph == 1) validate<32 - NB1>(&A[NB1], XROW(X_X1 + NB1), [](int i) { return 32 * i; }, par);
                    if (ph < 2) {
#pragma unroll
                        for (int c = 0; c < 4; ++c) ln_mod(A[4 * i + c], cs[c], ln);
                        if (i < 7) {
#pragma unroll
                            for (int c = 0; c < 4; ++c) cs[c] = lds128(tab + (4 * i + 4 + c) * 64);
                        }
                    }
                    mbar_wait(bars + 8 * (B_FULL + slot), (i >= 3 && ph == 2) ? 1 : 0);
                    const uint64_t d = DB0(gridDim.z - 1) + slot * 1024;
                    WG_FENCE();
#pragma unroll
                    for (int c = 0; c < 4; ++c) {
                        if (i == 0 && c == 0) wgmma128<0>(acc, A[4 * i + c], d);
                        else wgmma128<1>(acc, A[4 * i + c], d + c * 128);
                    }
                    WG_COMMIT();
                    if (i > 1) {
                        WG_WAIT(2);
                        RELEASE(prev, 1);
                    }
                }
                WG_WAIT(0);
                pin<64>(acc);
                RELEASE(ph == 2 ? 3 : 6, 2);
            }
            if (ph) {
                uint4 hv[4];
#pragma unroll
                for (int c = 0; c < 4; ++c) { hv[c] = gate8(&acc[8 * c], &acc[32 + 8 * c]); hv[c].x = tagw(hv[c].x, par); }
#pragma unroll
                for (int c = 0; c < 4; ++c) st_rlx(XR2(r * 12 + 4 * ph, X_HH - 4 + c), hv[c].x, hv[c].y, hv[c].z, hv[c].w);
                continue;
            }
            uint4 qf;
            const uint32_t qs = sb + OUT_OFF + threadIdx.x * 16;
            {
                const uint32_t kvw = sb + KV_OFF + (16 + w) * 1024 + ((lane >> 3) & 1) * 512 + (lane >> 4) * 128 + (lane & 7) * 16;
                const uint32_t km = t ? ~0u : ~1u, kp = t ? 0u : par;
#pragma unroll
                for (int q = 0; q < 8; ++q) {
                    const int i = (q >> 1) + 4 * (q & 1);
                    if (q == 0) mbar_wait(bars + 8 * (B_EMPTY + 2), 0);
                    if (q == 2) {
                        fence_async_smem();
                        __syncwarp();
                        if (j < 15 && elect()) {
                            bulk_s2g(g_kv + (size_t)bid * 2048 + w * 64, sb + KV_OFF + (16 + w) * 1024, 1024);
                            asm volatile("cp.async.bulk.commit_group;" ::: "memory");
                        }
                        mbar_wait(bars + 8 * (B_EMPTY + 6), 0);
                    }
                    const uint4 v = pack8(&acc[8 * i]);
                    stsm4(kvw + (i & 3) * 24576 + (i >> 2) * 256, (v.x & km) | kp, (v.y & km) | kp, (v.z & km) | kp, (v.w & km) | kp);
                }
                if (w < 3) {
                    const uint32_t id = (2 * t == g ? 0x3f80u : 0u) | (2 * t + 1 == g ? 0x3f800000u : 0u);
                    *(uint32_t*)(smem + ONES_OFF + threadIdx.x * 4) = (w & 1) ? 0u : id;
                }
                if (__builtin_expect(j < 2, 0)) {
#pragma unroll 1
                    for (int i = 0; i < 8 * (2 - j); ++i)
                        sts128(sb + KV_OFF + (i & 3) * 24576 + (i >> 2) * 4096 + threadIdx.x * 16, 0, 0, 0, 0);
                }
                fence_async_smem();
                __syncwarp();
                mbar_arrive1(bars + 8 * B_KVW);
                float accq[32];
#pragma unroll
                for (int q = 0; q < 4; ++q) {
                    const int slot = (8 + q) % NSTAGE;
                    mbar_wait(bars + 8 * (B_FULL + slot), q == 3 ? 1 : 0);
                    const uint64_t d = DB0(blockIdx.y) + slot * 1024;
                    WG_FENCE();
#pragma unroll
                    for (int s = 0; s < 8; ++s) {
                        if (q == 0 && s == 0) wgmma64<0>(accq, A[8 * q + s], d);
                        else wgmma64<1>(accq, A[8 * q + s], d + s * 128);
                    }
                }
                WG_COMMIT();
                WG_WAIT(0);
                pin<32>(accq);
                RELEASE(8, 3); RELEASE(0, 1);
#pragma unroll
                for (int i = 0; i < 32; ++i) accq[i] *= 0.25f * 1.4426950408889634f;
                qf = pack8(accq);
#pragma unroll
                for (int h = 1; h < 4; ++h) {
                    const uint4 v = pack8(&accq[8 * h]);
                    sts128(qs + (h - 1) * 4096, v.x, v.y, v.z, v.w);
                }
            }
            uint4* const st_own = XROW(X_ST) - lane + r * 8 + g;

            {
                const int wg = w >> 2, w4 = w & 3;
                const bool pC = 2 * t <= g, pD = 2 * t + 1 <= g;
                const uint32_t mD = (pC ? 0xffffu : 0u) | (pD ? 0xffff0000u : 0u);
                const uint32_t lk = sb + KV_OFF + w4 * 1024 + (lane >> 4) * 512 + ((lane >> 3) & 1) * 128 + (lane & 7) * 16;
                const uint32_t lv = sb + KV_OFF + w4 * 1024 + ((lane >> 3) & 1) * 512 + (lane >> 4) * 128 + (lane & 7) * 16 + 256;
                st_rlx(XR2(4 * r, X_O + 2), par ^ 1u, 0, 0, 0);
                st_rlx(XR2(4 * r, X_O + 3), par ^ 1u, 0, 0, 0);
                if (t == 0) st_rlx(st_own, par ^ 1u, 0, 0, 0);
                asm volatile("cp.async.bulk.wait_group.read 0;" ::: "memory");
                bar_sync(1, 256);
                bar_sync_if(wg == 0, 2, 256);
                uint32_t units = wg ? UNITS1 : UNITS0;
                int again = 0;
#pragma unroll 1
                while (true) {
                    const int h = units & 3, hf = (units >> 2) & 1;
                    const int b0 = 16 - 8 * j - 4 * hf - w4;
                    const uint32_t ka = lk + h * 24576 + hf * 4096, va = lv + h * 24576 + hf * 4096;
                    const uint4 qn = lds128(qs + (((units >> 4) & 3) - 1) * 4096 + (((units >> 6) & 1) - wg) * 2048);
                    mbar_wait(bars + 8 * (B_HLD + h), 0);
                    float O[8], L[4];
#pragma unroll
                    for (int b = 1; b < 16; ++b) {
                        float S[8];
                        mma2<0>(S, qf, ldsm4(ka + b * 1024));
                        const uint4 P = exp_pack(S);
                        const uint32_t on = b < b0 ? 0u : 0x3f803f80u;
                        if (b == 1) { mma2<0>(O, P, ldsm4t(va + b * 1024)); mma2<0, 1>(L, P, make_uint4(on, on, 0u, 0u)); }
                        else { mma2<1>(O, P, ldsm4t(va + b * 1024)); mma2<1, 1>(L, P, make_uint4(on, on, 0u, 0u)); }
                        if (b == 8) {
                            float N[8];
                            mma2<0>(S, qf, ldsm4(ka + 16384));
                            mma2<0>(N, qf, ldsm4(ka));
                            S[0] = pC ? S[0] : N[0]; S[1] = pD ? S[1] : N[1]; S[4] = N[4]; S[5] = N[5];
                            S[6] = pC ? S[6] : N[6]; S[7] = pD ? S[7] : N[7];
                            const uint4 Q = exp_pack(S);
                            const uint4 Po = make_uint4(Q.x & ~mD, 0u, Q.z, Q.w & ~mD), Pn = make_uint4(Q.x & mD, Q.y, 0u, Q.w & mD);
                            const uint32_t o0 = b0 > 0 ? 0u : 0x3f803f80u;
                            mma2<1>(O, Pn, ldsm4t(va + 16384));
                            mma2<1, 1>(L, Pn, make_uint4(0x3f803f80u, 0x3f803f80u, 0u, 0u));
                            mma2<1>(O, Po, ldsm4t(va));
                            mma2<1, 1>(L, Po, make_uint4(o0, o0, 0u, 0u));
                            bar_arrive_if((units & 7) + 8 * again == 4, 2, 256);
                        }
                    }
                    if (__builtin_expect(__any_sync(~0u, (f2u(L[0]) >> 23) - 79u > 96u || (f2u(L[2]) >> 23) - 79u > 96u), 0)) {
                        float m0 = -3e38f, m1 = -3e38f;
#pragma unroll 1
                        for (int pass = 0; pass < 2; ++pass) {
#pragma unroll
                            for (int i = 0; i < 8; ++i) O[i] = 0.f;
#pragma unroll
                            for (int i = 0; i < 4; ++i) L[i] = 0.f;
#pragma unroll 1
                            for (int b = max(b0, 0); b <= 16; ++b) {
                                float S[8];
                                mma2<0>(S, qf, ldsm4(ka + b * 1024));
                                const bool dg = b == 16, od = b == 0;
                                if ((dg && !pC) || (od && pC)) S[0] = S[6] = -3e38f;
                                if ((dg && !pD) || (od && pD)) S[1] = S[7] = -3e38f;
                                if (od) S[2] = S[3] = -3e38f;
                                if (dg) S[4] = S[5] = -3e38f;
                                if (pass == 0) { maxb<1>(S, m0, m1); continue; }
#pragma unroll
                                for (int i = 0; i < 8; ++i) S[i] -= (i & 2) ? m1 : m0;
                                const uint4 P = exp_pack(S);
                                mma2<1>(O, P, ldsm4t(va + b * 1024));
                                mma2<1, 1>(L, P, make_uint4(0x3f803f80u, 0x3f803f80u, 0u, 0u));
                            }
#pragma unroll
                            for (int o = 1; o < 4; o <<= 1) { m0 = fmaxf(m0, __shfl_xor_sync(~0u, m0, o)); m1 = fmaxf(m1, __shfl_xor_sync(~0u, m1, o)); }
                        }
                    }
                    mbar_wait(bars + 8 * (B_HALO + h), 0);
                    if (__builtin_expect(((volatile unsigned char*)smem)[MISC_OFF + 4 + h] > again, 0)) { again = 1; continue; }
                    again = 0;
                    const float i0 = rcpf(L[0]), i1 = rcpf(L[2]);
                    st_rlx(XR2(4 * r + h + (hf - wg) * 4 * X_ROWS, X_O), tagw(pack2(O[0] * i0, O[1] * i0), par), pack2(O[2] * i1, O[3] * i1),
                           pack2(O[4] * i0, O[5] * i0), pack2(O[6] * i1, O[7] * i1));
                    mbar_arrive_lt(bars + 8 * (B_EMPTY + 1 + h + (h >> 1) + lane), lane, h < 3 ? 1 + (h & 1) : 0);
                    qf = qn;
                    units = __shfl_sync(~0u, units >> 4, 0);
                    if (units < 16) break;
                }
            }

            {
                uint4 xr[4];
#pragma unroll
                for (int c = 0; c < 4; ++c) xr[c] = ld_rlx(XR2(4 * r, X_XR + c));
                float acc[32];
#pragma unroll
                for (int m = 0; m < 4; ++m) mbar_wait(bars + 8 * (B_FULL + 7 + m), 1);
                const uint64_t d0 = DB0(blockIdx.z) + 7 * 1024;
#pragma unroll
                for (int h = 0; h < 4; ++h) {
                    if ((h & 1) == 0) {
                        poll<16>(&A[8 * h], XROW(X_O + h), [](int i) { return 128 * (i & 7) + 32 * (i >> 3); }, par);
                        WG_FENCE();
                    }
#pragma unroll
                    for (int i = 0; i < 8; ++i) {
                        if (h == 0 && i == 0) wgmma64<0>(acc, A[8 * h + i], d0);
                        else wgmma64<1>(acc, A[8 * h + i], d0 + i * 512 + h * 128);
                    }
                }
                WG_COMMIT();
                RELEASE(5, 2);
                mbar_wait(bars + 8 * B_TAB2, 0);
                WG_WAIT(0);
                pin<32>(acc);
                RELEASE(7, 4);
                bar_arrive_if(w >= 4, 4, 256);
                float s0 = 0.f, s1 = 0.f, q0 = 0.f, q1 = 0.f;
                uint32_t xo[16];
#pragma unroll
                for (int b = 0; b < 8; ++b) {
                    const float2 ga = *(const float2*)(smem + GA_OFF + (8 * b + 2 * t) * 4);
                    const uint32_t u0 = (b & 1) ? xr[b >> 1].z : xr[b >> 1].x, u1 = (b & 1) ? xr[b >> 1].w : xr[b >> 1].y;
                    const float v0 = fmaf(ga.x, acc[4 * b], bf_lo(u0)), v1 = fmaf(ga.y, acc[4 * b + 1], bf_hi(u0));
                    const float v2 = fmaf(ga.x, acc[4 * b + 2], bf_lo(u1)), v3 = fmaf(ga.y, acc[4 * b + 3], bf_hi(u1));
                    xo[2 * b] = pack2(v0, v1);
                    xo[2 * b + 1] = pack2(v2, v3);
                    s0 += v0 + v1; q0 = fmaf(v0, v0, fmaf(v1, v1, q0));
                    s1 += v2 + v3; q1 = fmaf(v2, v2, fmaf(v3, v3, q1));
                }
#pragma unroll
                for (int i = 0; i < 3; ++i) sts128(qs + i * 4096, xo[4 * i], xo[4 * i + 1], xo[4 * i + 2], xo[4 * i + 3]);
                x1k = make_uint4(xo[12], xo[13], xo[14], xo[15]);
#pragma unroll
                for (int i = 0; i < 4; ++i) xo[4 * i] = tagw(xo[4 * i], par);
#pragma unroll
                for (int i = 0; i < 4; ++i) st_rlx(XR2(4 * r, X_X1 + i), xo[4 * i], xo[4 * i + 1], xo[4 * i + 2], xo[4 * i + 3]);
#pragma unroll
                for (int o = 1; o < 4; o <<= 1) {
                    s0 += __shfl_xor_sync(~0u, s0, o); q0 += __shfl_xor_sync(~0u, q0, o);
                    s1 += __shfl_xor_sync(~0u, s1, o); q1 += __shfl_xor_sync(~0u, q1, o);
                }
                if (t == 0) st_rlx(st_own, tagw(f2u(q0), par), f2u(s0), f2u(q1), f2u(s1));
            }
            ln.rs0 = ln.nm0 = ln.rs1 = ln.nm1 = 0;
        }
        const uint4* const hp = XR2((r & 6) * 12, X_HH);
        auto off8 = [](int k) { return ((k >> 2) * 12 + (k & 3)) * 32; };
        {
            float ag[24], au[24];
#pragma unroll
            for (int i = 0; i < 8; ++i) {
                const int n = 38 + i;
                mbar_wait(bars + 8 * (B_FULL + n % NSTAGE), (n / NSTAGE) & 1);
                const uint64_t d = DB0(gridDim.y - 1) + (n % NSTAGE) * 1024;
                WG_FENCE();
#pragma unroll
                for (int c = 0; c < 4; ++c) {
                    if (i == 0 && c == 0) {
                        wgmma48<0>(ag, A[4 * i + c], d);
                        wgmma48<0>(au, A[4 * i + c], d + 512);
                    } else {
                        wgmma48<1>(ag, A[4 * i + c], d + c * 128);
                        wgmma48<1>(au, A[4 * i + c], d + 512 + c * 128);
                    }
                }
                WG_COMMIT();
                if (i < 3) st_rlx(XR2(r * 12, X_HH + 8 + i), par ^ 1u, 0, 0, 0);
                else if (i < 7) st_rlx(XR2(((r + 6) & 7) * 12, X_PT + 5 + i), par ^ 1u, 0, 0, 0);
                if (i > 0) {
                    WG_WAIT(1);
                    RELEASE((n - 1) % NSTAGE, 1);
                }
                if (i == 2 || i == 4) {
#pragma unroll
                    for (int c = 0; c < 8; ++c) A[4 * i - 8 + c] = ld_rlx(hp + 64 * (i - 2) + off8(c));
                }
            }
            WG_WAIT(0);
            pin<24>(ag); pin<24>(au);
            RELEASE(45 % NSTAGE, 1);
#pragma unroll
            for (int c = 0; c < 3; ++c) A[16 + c] = gate8(&ag[8 * c], &au[8 * c]);
        }
        {
            float acc[32];
            uint4 Q[12], X1[4];
#pragma unroll
            for (int c = 0; c < 3; ++c) {
                A[16 + c].x = tagw(A[16 + c].x, par);
                st_rlx(XR2(r * 12, X_HH + 8 + c), A[16 + c].x, A[16 + c].y, A[16 + c].z, A[16 + c].w);
            }
#pragma unroll
            for (int p = 0; p < 2; ++p) {
                mbar_wait(bars + 8 * (B_FULL + (46 + p) % NSTAGE), 0);
                if (p == 0) validate<16>(A, hp, [](int k) { return (((k >> 2) & 1) * 12 + (k & 3) + (k >> 3) * 4) * 32; }, par);
                const uint64_t d = DB0(blockDim.z - 1) + ((46 + p) % NSTAGE) * 1024;
                WG_FENCE();
#pragma unroll
                for (int k = 0; k < 8; ++k) {
                    if (p == 0 && k == 0) wgmma64<0>(acc, A[0], d);
                    else wgmma64<1>(acc, A[8 * p + k], d + k * 128);
                }
            }
            WG_COMMIT();
            WG_WAIT(0);
            pin<32>(acc);
            RELEASE(46 % NSTAGE, 1);
            int slot = 48 % NSTAGE, fpar = 0;
#pragma unroll 1
            for (int cb = 0; cb < 3; ++cb) {
                float af[32];
#pragma unroll
                for (int p = 0; p < 3; ++p) {
                    mbar_wait(bars + 8 * (B_FULL + slot), fpar);
                    if (p == 2 && cb == 0) poll<3>(&A[19], XR2((r ^ 1) * 12, X_HH + 8), [](int c) { return 32 * c; }, par);
                    const uint64_t d = DB0(blockDim.y - 1) + slot * 1024;
                    if (++slot == NSTAGE) { slot = 0; fpar = 1; }
                    WG_FENCE();
#pragma unroll
                    for (int k = 0; k < (p < 2 ? 8 : 6); ++k) {
                        if (p == 0 && k == 0) wgmma64<0>(af, A[k], d);
                        else if (p < 2) wgmma64<1>(af, A[8 * p + k], d + k * 128);
                        else wgmma64<1>(af, A[16 + k], d + ((k / 3) ^ (r & 1)) * 512 + (k % 3) * 128);
                    }
                }
                WG_COMMIT();
                WG_WAIT(0);
                pin<32>(af);
                uint4* dst = XR2(((r + 2 + 2 * cb) & 7) * 12 + 4 * cb, X_PT);
#pragma unroll
                for (int c = 0; c < 4; ++c) {
                    const uint4 v = pack8(&af[8 * c]);
                    st_rlx(dst + c * 32, tagw(v.x, par), v.y, v.z, v.w);
                }
            }
            {
                mbar_wait(bars + 8 * (B_FULL + 57 % NSTAGE), 1);
                const uint64_t d = DB0(gridDim.z - 1) + (57 % NSTAGE) * 1024;
                WG_FENCE();
#pragma unroll
                for (int k = 0; k < 6; ++k) wgmma64<1>(acc, A[16 + k], d + ((k / 3) ^ (r & 1)) * 512 + (k % 3) * 128);
                WG_COMMIT();
            }
            const uint64_t did = cdesc(sb + ONES_OFF + blockIdx.y * 16, 128, 128);
#pragma unroll
            for (int i = 0; i < 3; ++i) X1[i] = lds128(sb + OUT_OFF + threadIdx.x * 16 + i * 4096);
            X1[3] = x1k;
            poll<12>(Q, XR2(r * 12, X_PT), [](int i) { return 32 * i; }, par);
            float ap[4][8];
            WG_FENCE();
#pragma unroll
            for (int i = 0; i < 12; ++i) {
                if (i < 4) wgmma16<0>(ap[i], Q[i], did);
                else wgmma16<1>(ap[i & 3], Q[i], did);
            }
            WG_COMMIT();
            WG_WAIT(0);
            pin<32>(&ap[0][0]); pin<32>(acc);
            const uint32_t stg = sb + OUT_OFF + w * 512;
            uint32_t ln2;
            asm volatile("mov.u32 %0, %%laneid;" : "=r"(ln2));
            char* const op = (char*)out + (size_t)(128 * j + 16 * w) * 1024 + 128 * r + (ln2 >> 2) * 1024 + (ln2 & 3) * 16;
            __syncwarp();
#pragma unroll
            for (int hf = 0; hf < 2; ++hf) {
#pragma unroll
                for (int i = 2 * hf; i < 2 * hf + 2; ++i) {
                    const uint32_t xw[4] = {X1[i].x, X1[i].y, X1[i].z, X1[i].w};
                    uint32_t o[4];
#pragma unroll
                    for (int e = 0; e < 4; ++e) {
                        const float2 gb = *(const float2*)(smem + GB_OFF + (16 * i + 8 * (e >> 1) + 2 * t) * 4);
                        o[e] = pack2(fmaf(gb.x, acc[8 * i + 2 * e] + ap[i][2 * e], bf_lo(xw[e])),
                                     fmaf(gb.y, acc[8 * i + 2 * e + 1] + ap[i][2 * e + 1], bf_hi(xw[e])));
                    }
                    stsm4(stg + (lane & 8) * 512 + (lane & 7) * 64 + (((2 * (i & 1) + (lane >> 4)) ^ (lane >> 1)) & 3) * 16, o[0], o[1], o[2], o[3]);
                }
                __syncwarp();
#pragma unroll
                for (int k = 0; k < 2; ++k) {
                    const uint4 v = lds128(stg + k * 4096 + g * 64 + ((t ^ (g >> 1)) & 3) * 16);
                    *(uint4*)(op + k * 8192 + 64 * hf) = v;
                }
                __syncwarp();
            }
            mbar_arrive1(bars + 8 * B_DONE);
        }
    } else {
        asm volatile("setmaxnreg.dec.sync.aligned.u32 40;");
        if (warp == 8) {
            uint4 tb[2];
            tb[0] = __ldg(&c_sched[lane]); tb[1] = __ldg(&c_sched[32 + lane]);
#pragma unroll
            for (int q = 0; q < 2; ++q) {
                const uint32_t c = ((tb[q].x & 0xffffu) + (tb[q].y & 255u) * r) & (tb[q].y >> 16);
                const uint32_t cr = c + (((tb[q].x >> 16) + ((tb[q].y >> 8) & 255u) * (r & 6)) << 16);
                if (q == 0 || lane < 26) sts128(sb + SCHED_OFF + q * 512 + lane * 16, cr, cr + tb[q].z, tb[q].w, 0);
            }
            __syncwarp();
            bar_arrive(3, 128);
        } else {
            bar_sync(3, 128);
            mbar_wait(bars + 8 * B_GO, 0);
            const unsigned epoch = *s_epoch;
            if (warp < 11) {
                const int nn = j < 2 ? j : 2;
                const unsigned* fl = (const unsigned*)(g_kv + (size_t)(bid - 8 * ((lane >> 3) + 1)) * 2048 + (lane & 7) * 64 + 63);
                unsigned fv = epoch, fv2 = epoch;
                if (lane < 8 * nn) { fv = ld_u32(fl + (10 - warp) * 2048); fv2 = ld_u32(fl + (12 - warp) * 2048); }
                mbar_wait(bars + 8 * (warp == 9 ? B_KVW : B_EMPTY + 5), 0);
                if (warp == 9 && elect()) {
                    if (j < 15) {
#pragma unroll 1
                        for (int h = 1; h < 4; ++h) {
                            if (h < 3) __nanosleep(PUBGAP);
                            bulk_s2g(g_kv + (size_t)bid * 2048 + h * 512, sb + KV_OFF + h * 24576 + 16384, 8192);
                        }
                        asm volatile("cp.async.bulk.commit_group;" ::: "memory");
                    }
                }
                uint32_t hb = 0, rph = 0;
#pragma unroll 1
                for (int h = 10 - warp; h < 4;) {
#pragma unroll 1
                    while ((fv ^ epoch) & 1u) fv = ld_u32(fl + h * 2048);
                    __syncwarp();
                    const uint32_t lb = hb ? hb : bars + 8 * (B_HLD + h);
                    if (elect()) {
                        mbar_expect(lb, nn * 8192);
#pragma unroll 1
                        for (int n = 1; n <= nn; ++n)
                            bulk_g2s(sb + KV_OFF + h * 24576 + (2 - n) * 8192, g_kv + (size_t)(bid - 8 * n) * 2048 + h * 512, 8192, lb);
                    }
                    mbar_wait(lb, hb ? rph : 0);
                    if (hb) rph ^= 1;
                    uint32_t bad = 0;
#pragma unroll 1
                    for (int n = 1; n <= nn; ++n) {
#pragma unroll
                        for (int i = 0; i < 16; ++i) bad |= lds32(sb + KV_OFF + h * 24576 + (2 - n) * 8192 + lane * 16 + i * 512) ^ epoch;
                    }
                    if (__any_sync(~0u, bad & 1u)) { hb = bars + 8 * (B_HRT + warp - 9); continue; }
                    smem[MISC_OFF + 4 + h] = hb != 0;
                    __syncwarp();
                    mbar_arrive1(bars + 8 * (B_HALO + h));
                    hb = 0;
                    h += 2;
                    fv = fv2;
                }
                if (warp == 9) {
                    asm volatile("cp.async.bulk.wait_group.read 0;" ::: "memory");
                    __syncwarp();
                    mbar_arrive1(bars + 8 * B_PUB);
                }
            } else {
                const uint32_t par = epoch & 1u;
                if (lane < 8) {
                    const char* p = lane < 4 ? (const char*)(wmod + (size_t)(4 * bid + lane) * 3072 + 1024)
                                  : lane == 4 ? (const char*)wo + bid * 4096
                                  : (const char*)(lane == 5 ? wg : lane == 6 ? wu : wd) + bid * 11008;
                    prefetch_l2(p, lane < 5 ? 4096 : 11008);
                }
                mbar_wait(bars + 8 * (B_FULL + 5), 0);
                {
                    const int half = lane & 1, rg = lane >> 1;
                    float a[8];
#pragma unroll
                    for (int k = 0; k < 8; ++k) a[k] = 0.f;
#pragma unroll 1
                    for (int b = 0; b < 8; ++b) {
                        const int row = b * 64 + rg * 4;
                        uint4 wv[4];
#pragma unroll
                        for (int i = 0; i < 4; ++i) wv[i] = ldg_nc(wmod + (size_t)(row + i) * 3072 + 1024 + 16 * bid + 8 * half);
                        const uint2 cv = *(const uint2*)(cvec + row);
                        fma8(a, silu_bf(bf_lo(cv.x)), wv[0]); fma8(a, silu_bf(bf_hi(cv.x)), wv[1]);
                        fma8(a, silu_bf(bf_lo(cv.y)), wv[2]); fma8(a, silu_bf(bf_hi(cv.y)), wv[3]);
                    }
                    red8(a, lane);
                    float* red2 = (float*)(smem + RED_OFF + 512);
                    if ((lane & 2) == 0) red2[half * 8 + (lane >> 2)] = a[0];
                    __syncwarp();
                    if (lane < 4) {
                        const uint4 v = *(const uint4*)(red2 + 4 * lane);
                        st_rlx(&g_m2[4 * bid + lane], tagw(v.x, par), v.y, v.z, v.w);
                    }
                    __syncwarp();
                }
                uint32_t* tab2 = (uint32_t*)(smem + TAB2_OFF);
                __nanosleep(GSLP);
#pragma unroll 1
                for (int q = 0; q < 9; ++q) {
                    const int e = q < 8 ? 128 + q * 32 + lane : (lane < 16 ? 16 * r + lane : 368 + 16 * r + lane);
                    uint4 v;
                    poll<1>(&v, &g_m2[e], [](int) { return 0; }, par);
                    uint32_t v0 = pack2(u2f(v.x), u2f(v.y)), v1 = pack2(u2f(v.z), u2f(v.w));
                    if (q < 8) {
                        const int ep = (q & 3) * 64 + lane * 2;
                        const int isc = q >> 2;
                        if (isc) { v0 = one_plus(v0); v1 = one_plus(v1); }
                        const int kap = ep >> 3, wi = ep & 7;
                        const int o0 = (kap * 4 + (wi & 3)) * 4 + (wi >> 2) + (isc ? 0 : 2);
                        tab2[o0] = v0;
                        tab2[o0 + 4] = v1;
                    } else {
                        *(float4*)(smem + GA_OFF + lane * 16) = make_float4(bf_lo(v0), bf_hi(v0), bf_lo(v1), bf_hi(v1));
                    }
                }
                __syncwarp();
                if (lane == 0) mbar_arrive(bars + 8 * B_TAB2);
            }
        }
        if (warp < 11 && elect()) {
            uint32_t a = sb + SCHED_OFF + (warp == 8 ? 0 : (10 + warp) * 16);
            uint4 en = lds128(a);
#pragma unroll 1
            while (a < sb + SCHED_OFF + 58 * 16) {
                const uint4 e = en;
                a += a < sb + SCHED_OFF + 18 * 16 ? 16 : 48;
                en = lds128(a);
                const uint32_t slot = e.z & 15u, fb = bars + 8 * B_FULL + 8 * slot, dst = sb + slot * STAGE_BYTES;
                if (e.z & 0xff00u) mbar_wait_b(bars + ((e.z >> 5) & 0x7f8u), 0);
                mbar_wait_b(fb + 8 * (B_EMPTY - B_FULL), (e.z >> 5) & 1u);
                mbar_expect(fb, (e.z << 10) & STAGE_BYTES);
                if (e.z & 16u) {
                    tma2d(dst, &tm.m[(e.z >> 16) & 15u], e.x & 0xffffu, e.x >> 16, fb);
                    tma2d(dst + 8192, &tm.m[e.z >> 24], e.y & 0xffffu, e.y >> 16, fb);
                }
            }
            mbar_wait_b(bars + 8 * B_DONE, 0);
        }
    }
}

typedef CUresult (*EncodeFn)(CUtensorMap*, CUtensorMapDataType, cuuint32_t, void*, const cuuint64_t*, const cuuint64_t*,
                             const cuuint32_t*, const cuuint32_t*, CUtensorMapInterleave, CUtensorMapSwizzle,
                             CUtensorMapL2promotion, CUtensorMapFloatOOBfill);

void make2d(EncodeFn enc, CUtensorMap* m, const void* p, uint64_t cols, uint64_t rows, uint32_t box_rows = 64) {
    cuuint64_t dims[2] = {cols, rows};
    cuuint64_t str[1] = {cols * 2};
    cuuint32_t box[2] = {64, box_rows}, es[2] = {1, 1};
    enc(m, CU_TENSOR_MAP_DATA_TYPE_BFLOAT16, 2, (void*)p, dims, str, box, es, CU_TENSOR_MAP_INTERLEAVE_NONE,
        CU_TENSOR_MAP_SWIZZLE_128B, CU_TENSOR_MAP_L2_PROMOTION_L2_128B, CU_TENSOR_MAP_FLOAT_OOB_FILL_NONE);
}

}

extern "C" void kernel_launch(void* const* d_in, const int* in_sizes, int n_in, void* d_out, int out_size) {
    const __nv_bfloat16* x = (const __nv_bfloat16*)d_in[0];
    const __nv_bfloat16* wqkv = (const __nv_bfloat16*)d_in[1];
    const __nv_bfloat16* wo = (const __nv_bfloat16*)d_in[2];
    const __nv_bfloat16* wg = (const __nv_bfloat16*)d_in[4];
    const __nv_bfloat16* wu = (const __nv_bfloat16*)d_in[5];
    const __nv_bfloat16* wd = (const __nv_bfloat16*)d_in[6];
    const __nv_bfloat16* c = (const __nv_bfloat16*)d_in[7];
    const __nv_bfloat16* wmod = (const __nv_bfloat16*)d_in[8];

    void* fn = nullptr;
    cudaDriverEntryPointQueryResult qr;
    cudaGetDriverEntryPoint("cuTensorMapEncodeTiled", &fn, cudaEnableDefault, &qr);
    EncodeFn enc = (EncodeFn)fn;
    Maps tm;
    make2d(enc, &tm.m[0], x, 512, 2048, 128);
    make2d(enc, &tm.m[1], wqkv, 1536, 512);
    make2d(enc, &tm.m[2], wo, 512, 512);
    make2d(enc, &tm.m[3], wg, 1376, 512);
    make2d(enc, &tm.m[4], wu, 1376, 512);
    make2d(enc, &tm.m[5], wd, 512, 1376);
    cudaFuncSetAttribute(fused_kernel, cudaFuncAttributeMaxDynamicSharedMemorySize, SMEM_BYTES);
    fused_kernel<<<128, 384, SMEM_BYTES, cudaStreamPerThread>>>(x, wqkv, wo, wg, wu, wd, c, wmod, (__nv_bfloat16*)d_out, tm);
}
```

```cpp
#include <cuda_runtime.h>
#include <cuda_bf16.h>
#include <cuda.h>
#include <stdint.h>

namespace {

constexpr int NSTAGE = 11;
constexpr int STAGE_BYTES = 16384;
constexpr int KV_OFF = 1 * STAGE_BYTES;
constexpr int OUT_OFF = NSTAGE * STAGE_BYTES;
constexpr int TAB1_OFF = OUT_OFF + 12288;
constexpr int TAB2_OFF = TAB1_OFF + 2048;
constexpr int GA_OFF = TAB2_OFF + 2048;
constexpr int GB_OFF = GA_OFF + 256;
constexpr int ONES_OFF = GB_OFF + 256;
constexpr int RED_OFF = TAB2_OFF;
constexpr int SCHED_OFF = ONES_OFF + 384;
constexpr int MISC_OFF = SCHED_OFF + 58 * 16;
constexpr int BAR_OFF = MISC_OFF + 16;
constexpr int B_FULL = 0, B_HALO = 11, B_PUB = 15, B_HLD = 16, B_HRT = 20;
constexpr int B_EMPTY = 22, B_KVW = 33, B_GO = 34, B_DONE = 35, B_TAB2 = 36, B_XF = 38, NBAR = 40;
constexpr int SMEM_BYTES = BAR_OFF + NBAR * 8;

#define NB1 12
#define UNITS0 0x2210
#define UNITS1 0x776354
#define PUBGAP 150
constexpr int SPIN_LIMIT = 1 << 21;
#define DIE() asm volatile("st.global.u32 [%0], %1;" ::"l"(0ull), "r"(0) : "memory")

__device__ const uint4 c_sched[64] = {
    {512u | 0u << 16, 64u | 0u << 8 | 4095u << 16, 512u | 0u << 16, 0u | 1u << 4 | 1u << 5 | (0) << 8 | 1u << 16 | 1u << 24},
    {512u | 64u << 16, 64u | 0u << 8 | 4095u << 16, 512u | 0u << 16, 1u | 1u << 4 | 1u << 5 | (0) << 8 | 1u << 16 | 1u << 24},
    {512u | 128u << 16, 64u | 0u << 8 | 4095u << 16, 512u | 0u << 16, 2u | 1u << 4 | 1u << 5 | (0) << 8 | 1u << 16 | 1u << 24},
    {512u | 192u << 16, 64u | 0u << 8 | 4095u << 16, 512u | 0u << 16, 3u | 1u << 4 | 1u << 5 | (B_GO) << 8 | 1u << 16 | 1u << 24},
    {512u | 256u << 16, 64u | 0u << 8 | 4095u << 16, 512u | 0u << 16, 4u | 1u << 4 | 1u << 5 | (0) << 8 | 1u << 16 | 1u << 24},
    {512u | 320u << 16, 64u | 0u << 8 | 4095u << 16, 512u | 0u << 16, 5u | 1u << 4 | 1u << 5 | (0) << 8 | 1u << 16 | 1u << 24},
    {512u | 384u << 16, 64u | 0u << 8 | 4095u << 16, 512u | 0u << 16, 6u | 1u << 4 | 1u << 5 | (0) << 8 | 1u << 16 | 1u << 24},
    {512u | 448u << 16, 64u | 0u << 8 | 4095u << 16, 512u | 0u << 16, 7u | 1u << 4 | 1u << 5 | (0) << 8 | 1u << 16 | 1u << 24},
    {0u | 0u << 16, 64u | 0u << 8 | 4095u << 16, 0u | 64u << 16, 8u | 1u << 4 | 1u << 5 | (0) << 8 | 1u << 16 | 1u << 24},
    {0u | 128u << 16, 64u | 0u << 8 | 4095u << 16, 0u | 64u << 16, 9u | 1u << 4 | 1u << 5 | (0) << 8 | 1u << 16 | 1u << 24},
    {0u | 256u << 16, 64u | 0u << 8 | 4095u << 16, 0u | 64u << 16, 10u | 1u << 4 | 1u << 5 | (0) << 8 | 1u << 16 | 1u << 24},
    {0u | 384u << 16, 64u | 0u << 8 | 4095u << 16, 0u | 64u << 16, 0u | 1u << 4 | 0u << 5 | (0) << 8 | 1u << 16 | 1u << 24},
    {0u | 0u << 16, 0u | 0u << 8 | 4095u << 16, 0u | 0u << 16, 1u | 0u << 4 | 0u << 5 | (0) << 8 | 0u << 16 | 0u << 24},
    {0u | 0u << 16, 0u | 0u << 8 | 4095u << 16, 0u | 0u << 16, 2u | 0u << 4 | 0u << 5 | (0) << 8 | 0u << 16 | 0u << 24},
    {0u | 0u << 16, 0u | 0u << 8 | 4095u << 16, 0u | 0u << 16, 3u | 0u << 4 | 0u << 5 | (0) << 8 | 0u << 16 | 0u << 24},
    {0u | 0u << 16, 0u | 0u << 8 | 4095u << 16, 0u | 0u << 16, 4u | 0u << 4 | 0u << 5 | (0) << 8 | 0u << 16 | 0u << 24},
    {0u | 0u << 16, 0u | 0u << 8 | 4095u << 16, 0u | 0u << 16, 5u | 0u << 4 | 0u << 5 | (0) << 8 | 0u << 16 | 0u << 24},
    {0u | 0u << 16, 0u | 0u << 8 | 4095u << 16, 0u | 0u << 16, 6u | 0u << 4 | 0u << 5 | (0) << 8 | 0u << 16 | 0u << 24},
    {0u | 0u << 16, 64u | 0u << 8 | 4095u << 16, 0u | 64u << 16, 7u | 1u << 4 | 0u << 5 | (B_PUB) << 8 | 2u << 16 | 2u << 24},
    {0u | 128u << 16, 64u | 0u << 8 | 4095u << 16, 0u | 64u << 16, 8u | 1u << 4 | 0u << 5 | (0) << 8 | 2u << 16 | 2u << 24},
    {0u | 256u << 16, 64u | 0u << 8 | 4095u << 16, 0u | 64u << 16, 9u | 1u << 4 | 0u << 5 | (B_PUB) << 8 | 2u << 16 | 2u << 24},
    {0u | 384u << 16, 64u | 0u << 8 | 4095u << 16, 0u | 64u << 16, 10u | 1u << 4 | 0u << 5 | (0) << 8 | 2u << 16 | 2u << 24},
    {0u | 0u << 16, 176u | 0u << 8 | 4095u << 16, 0u | 0u << 16, 0u | 1u << 4 | 1u << 5 | (0) << 8 | 3u << 16 | 4u << 24},
    {0u | 64u << 16, 176u | 0u << 8 | 4095u << 16, 0u | 0u << 16, 1u | 1u << 4 | 1u << 5 | (0) << 8 | 3u << 16 | 4u << 24},
    {0u | 128u << 16, 176u | 0u << 8 | 4095u << 16, 0u | 0u << 16, 2u | 1u << 4 | 1u << 5 | (0) << 8 | 3u << 16 | 4u << 24},
    {0u | 192u << 16, 176u | 0u << 8 | 4095u << 16, 0u | 0u << 16, 3u | 1u << 4 | 1u << 5 | (0) << 8 | 3u << 16 | 4u << 24},
    {0u | 256u << 16, 176u | 0u << 8 | 4095u << 16, 0u | 0u << 16, 4u | 1u << 4 | 1u << 5 | (0) << 8 | 3u << 16 | 4u << 24},
    {0u | 320u << 16, 176u | 0u << 8 | 4095u << 16, 0u | 0u << 16, 5u | 1u << 4 | 1u << 5 | (0) << 8 | 3u << 16 | 4u << 24},
    {0u | 384u << 16, 176u | 0u << 8 | 4095u << 16, 0u | 0u << 16, 6u | 1u << 4 | 1u << 5 | (0) << 8 | 3u << 16 | 4u << 24},
    {0u | 448u << 16, 176u | 0u << 8 | 4095u << 16, 0u | 0u << 16, 7u | 1u << 4 | 1u << 5 | (0) << 8 | 3u << 16 | 4u << 24},
    {64u | 0u << 16, 176u | 0u << 8 | 4095u << 16, 0u | 0u << 16, 8u | 1u << 4 | 1u << 5 | (0) << 8 | 3u << 16 | 4u << 24},
    {64u | 64u << 16, 176u | 0u << 8 | 4095u << 16, 0u | 0u << 16, 9u | 1u << 4 | 1u << 5 | (0) << 8 | 3u << 16 | 4u << 24},
    {64u | 128u << 16, 176u | 0u << 8 | 4095u << 16, 0u | 0u << 16, 10u | 1u << 4 | 1u << 5 | (0) << 8 | 3u << 16 | 4u << 24},
    {64u | 192u << 16, 176u | 0u << 8 | 4095u << 16, 0u | 0u << 16, 0u | 1u << 4 | 0u << 5 | (0) << 8 | 3u << 16 | 4u << 24},
    {64u | 256u << 16, 176u | 0u << 8 | 4095u << 16, 0u | 0u << 16, 1u | 1u << 4 | 0u << 5 | (0) << 8 | 3u << 16 | 4u << 24},
    {64u | 320u << 16, 176u | 0u << 8 | 4095u << 16, 0u | 0u << 16, 2u | 1u << 4 | 0u << 5 | (0) << 8 | 3u << 16 | 4u << 24},
    {64u | 384u << 16, 176u | 0u << 8 | 4095u << 16, 0u | 0u << 16, 3u | 1u << 4 | 0u << 5 | (0) << 8 | 3u << 16 | 4u << 24},
    {64u | 448u << 16, 176u | 0u << 8 | 4095u << 16, 0u | 0u << 16, 4u | 1u << 4 | 0u << 5 | (0) << 8 | 3u << 16 | 4u << 24},
    {128u | 0u << 16, 176u | 0u << 8 | 4095u << 16, 0u | 0u << 16, 5u | 1u << 4 | 0u << 5 | (0) << 8 | 3u << 16 | 4u << 24},
    {128u | 64u << 16, 176u | 0u << 8 | 4095u << 16, 0u | 0u << 16, 6u | 1u << 4 | 0u << 5 | (0) << 8 | 3u << 16 | 4u << 24},
    {128u | 128u << 16, 176u | 0u << 8 | 4095u << 16, 0u | 0u << 16, 7u | 1u << 4 | 0u << 5 | (0) << 8 | 3u << 16 | 4u << 24},
    {128u | 192u << 16, 176u | 0u << 8 | 4095u << 16, 0u | 0u << 16, 8u | 1u << 4 | 0u << 5 | (0) << 8 | 3u << 16 | 4u << 24},
    {128u | 256u << 16, 176u | 0u << 8 | 4095u << 16, 0u | 0u << 16, 9u | 1u << 4 | 0u << 5 | (0) << 8 | 3u << 16 | 4u << 24},
    {128u | 320u << 16, 176u | 0u << 8 | 4095u << 16, 0u | 0u << 16, 10u | 1u << 4 | 0u << 5 | (0) << 8 | 3u << 16 | 4u << 24},
    {128u | 384u << 16, 176u | 0u << 8 | 4095u << 16, 0u | 0u << 16, 0u | 1u << 4 | 1u << 5 | (0) << 8 | 3u << 16 | 4u << 24},
    {128u | 448u << 16, 176u | 0u << 8 | 4095u << 16, 0u | 0u << 16, 1u | 1u << 4 | 1u << 5 | (0) << 8 | 3u << 16 | 4u << 24},
    {0u | 0u << 16, 64u | 176u << 8 | 511u << 16, 0u | 176u << 16, 2u | 1u << 4 | 1u << 5 | (0) << 8 | 5u << 16 | 5u << 24},
    {0u | 64u << 16, 64u | 176u << 8 | 511u << 16, 0u | 176u << 16, 3u | 1u << 4 | 1u << 5 | (0) << 8 | 5u << 16 | 5u << 24},
    {128u | 0u << 16, 64u | 176u << 8 | 511u << 16, 0u | 176u << 16, 4u | 1u << 4 | 1u << 5 | (0) << 8 | 5u << 16 | 5u << 24},
    {128u | 64u << 16, 64u | 176u << 8 | 511u << 16, 0u | 176u << 16, 5u | 1u << 4 | 1u << 5 | (0) << 8 | 5u << 16 | 5u << 24},
    {128u | 128u << 16, 64u | 176u << 8 | 511u << 16, 0u | 176u << 16, 6u | 1u << 4 | 1u << 5 | (0) << 8 | 5u << 16 | 5u << 24},
    {256u | 0u << 16, 64u | 176u << 8 | 511u << 16, 0u | 176u << 16, 7u | 1u << 4 | 1u << 5 | (0) << 8 | 5u << 16 | 5u << 24},
    {256u | 64u << 16, 64u | 176u << 8 | 511u << 16, 0u | 176u << 16, 8u | 1u << 4 | 1u << 5 | (0) << 8 | 5u << 16 | 5u << 24},
    {256u | 128u << 16, 64u | 176u << 8 | 511u << 16, 0u | 176u << 16, 9u | 1u << 4 | 1u << 5 | (0) << 8 | 5u << 16 | 5u << 24},
    {384u | 0u << 16, 64u | 176u << 8 | 511u << 16, 0u | 176u << 16, 10u | 1u << 4 | 1u << 5 | (0) << 8 | 5u << 16 | 5u << 24},
    {384u | 64u << 16, 64u | 176u << 8 | 511u << 16, 0u | 176u << 16, 0u | 1u << 4 | 0u << 5 | (0) << 8 | 5u << 16 | 5u << 24},
    {384u | 128u << 16, 64u | 176u << 8 | 511u << 16, 0u | 176u << 16, 1u | 1u << 4 | 0u << 5 | (0) << 8 | 5u << 16 | 5u << 24},
    {0u | 128u << 16, 64u | 176u << 8 | 511u << 16, 0u | 176u << 16, 2u | 1u << 4 | 0u << 5 | (0) << 8 | 5u << 16 | 5u << 24},
};

__device__ uint4 g_kv[16 * 8 * 2048];
constexpr int X_O = 0, X_X1 = 32, X_HH = 64, X_PT = 160, X_ST = 256, X_ROWS = 258;
__device__ uint4 g_x[16 * 8 * X_ROWS * 32];
__device__ uint4 g_m1[512];
__device__ uint4 g_m2[512];
__device__ uint4 g_rs[2048];
__device__ unsigned g_cnt;
#define PROF(i) do {} while (0)
#define PROF_DUMP() do {} while (0)
#define PROF_EXTRA 0
#define PROF2(i) do {} while (0)

__device__ __forceinline__ uint32_t s2u(const void* p) { return (uint32_t)__cvta_generic_to_shared(p); }
__device__ __forceinline__ bool elect() {
    uint32_t p;
    asm volatile("{\n.reg .pred p;\nelect.sync _|p, 0xffffffff;\nselp.u32 %0, 1, 0, p;\n}" : "=r"(p));
    return p;
}
__device__ __forceinline__ void mbar_init(uint32_t b, int c) {
    asm volatile("mbarrier.init.shared::cta.b64 [%0], %1;" ::"r"(b), "r"(c) : "memory");
}
__device__ __forceinline__ void mbar_expect(uint32_t b, uint32_t bytes) {
    asm volatile("mbarrier.arrive.expect_tx.shared::cta.b64 _, [%0], %1;" ::"r"(b), "r"(bytes) : "memory");
}
__device__ __forceinline__ void mbar_arrive1(uint32_t b) {
    asm volatile("{\n.reg .pred p;\nelect.sync _|p, 0xffffffff;\n@p mbarrier.arrive.shared::cta.b64 _, [%0];\n}" ::"r"(b) : "memory");
}
__device__ __forceinline__ void mbar_arrive_lt(uint32_t b, int a, int n) {
    asm volatile("{\n.reg .pred p;\nsetp.lt.s32 p, %1, %2;\n@p mbarrier.arrive.shared::cta.b64 _, [%0];\n}" ::"r"(b), "r"(a), "r"(n) : "memory");
}
__device__ __forceinline__ void mbar_wait(uint32_t b, uint32_t ph) {
    asm volatile("{\n.reg .pred p;\nLOOP_%=:\nmbarrier.try_wait.parity.shared::cta.b64 p, [%0], %1;\n@!p bra LOOP_%=;\n}"
                 ::"r"(b), "r"(ph) : "memory");
}
__device__ __forceinline__ void mbar_wait_b(uint32_t b, uint32_t ph) {
    asm volatile(
        "{\n.reg .pred p;\n.reg .u32 n;\n"
        "mov.u32 n, 0;\n"
        "LOOP_%=:\n"
        "mbarrier.try_wait.parity.shared::cta.b64 p, [%0], %1;\n"
        "@p bra DONE_%=;\n"
        "add.u32 n, n, 1;\n"
        "setp.lt.u32 p, n, %2;\n"
        "@p bra LOOP_%=;\n"
        "st.global.u32 [%3], n;\n"
        "DONE_%=:\n}" ::"r"(b), "r"(ph), "n"(SPIN_LIMIT), "l"(0ull) : "memory");
}
__device__ __forceinline__ void bar_sync(int id, int n) { asm volatile("bar.sync %0, %1;" ::"r"(id), "r"(n) : "memory"); }
__device__ __forceinline__ void bar_arrive(int id, int n) { asm volatile("bar.arrive %0, %1;" ::"r"(id), "r"(n) : "memory"); }
__device__ __forceinline__ void bar_sync_if(int c, int id, int n) {
    asm volatile("{\n.reg .pred p;\nsetp.ne.u32 p, %0, 0;\n@p bar.sync %1, %2;\n}" ::"r"(c), "r"(id), "r"(n) : "memory");
}
__device__ __forceinline__ void bar_arrive_if(int c, int id, int n) {
    asm volatile("{\n.reg .pred p;\nsetp.ne.u32 p, %0, 0;\n@p bar.arrive %1, %2;\n}" ::"r"(c), "r"(id), "r"(n) : "memory");
}
__device__ __forceinline__ void fence_async_smem() { asm volatile("fence.proxy.async.shared::cta;" ::: "memory"); }

__device__ __forceinline__ void tma2d(uint32_t dst, const CUtensorMap* m, int c0, int c1, uint32_t bar) {
    asm volatile("cp.async.bulk.tensor.2d.shared::cluster.global.mbarrier::complete_tx::bytes [%0], [%1, {%3, %4}], [%2];"
                 ::"r"(dst), "l"(m), "r"(bar), "r"(c0), "r"(c1) : "memory");
}
__device__ __forceinline__ void bulk_g2s(uint32_t dst, const void* src, uint32_t bytes, uint32_t bar) {
    asm volatile("cp.async.bulk.shared::cluster.global.mbarrier::complete_tx::bytes [%0], [%1], %2, [%3];"
                 ::"r"(dst), "l"(src), "r"(bytes), "r"(bar) : "memory");
}
__device__ __forceinline__ void bulk_s2g(void* dst, uint32_t src, uint32_t bytes) {
    asm volatile("cp.async.bulk.global.shared::cta.bulk_group [%0], [%1], %2;" ::"l"(dst), "r"(src), "r"(bytes) : "memory");
}
__device__ __forceinline__ void prefetch_l2(const void* p, uint32_t bytes) {
    asm volatile("cp.async.bulk.prefetch.L2.global [%0], %1;" ::"l"(p), "r"(bytes) : "memory");
}
__device__ __forceinline__ uint4 ldg_nc(const void* p) {
    uint4 v;
    asm volatile("ld.global.nc.v4.u32 {%0,%1,%2,%3}, [%4];" : "=r"(v.x), "=r"(v.y), "=r"(v.z), "=r"(v.w) : "l"(p));
    return v;
}
__device__ __forceinline__ unsigned ld_u32(const unsigned* p) {
    unsigned v;
    asm volatile("ld.relaxed.gpu.global.u32 %0, [%1];" : "=r"(v) : "l"(p) : "memory");
    return v;
}
__device__ __forceinline__ uint4 ld_rlx(const void* p) {
    uint4 v;
    asm volatile("ld.relaxed.gpu.global.v4.u32 {%0,%1,%2,%3}, [%4];" : "=r"(v.x), "=r"(v.y), "=r"(v.z), "=r"(v.w) : "l"(p) : "memory");
    return v;
}
__device__ __forceinline__ void st_rlx(void* p, uint32_t x, uint32_t y, uint32_t z, uint32_t w) {
    asm volatile("st.relaxed.gpu.global.v4.u32 [%0], {%1,%2,%3,%4};" ::"l"(p), "r"(x), "r"(y), "r"(z), "r"(w) : "memory");
}
__device__ __forceinline__ uint32_t tagw(uint32_t x, uint32_t par) {
    uint32_t d;
    asm("lop3.b32 %0, %1, 0xfffffffe, %2, 0xea;" : "=r"(d) : "r"(x), "r"(par));
    return d;
}
template <int N>
__device__ __forceinline__ bool stale(const uint4* v, uint32_t par) {
    uint32_t bad = 0;
#pragma unroll
    for (int i = 0; i < N; ++i) asm("lop3.b32 %0, %1, %2, %0, 0xbe;" : "+r"(bad) : "r"(v[i].x), "r"(par));
    return __any_sync(~0u, bad & 1u);
}
template <int N, class F>
__device__ __forceinline__ void poll(uint4* v, const uint4* p, F off, uint32_t par) {
#pragma unroll 1
    do {
#pragma unroll
        for (int i = 0; i < N; ++i) v[i] = ld_rlx(p + off(i));
    } while (stale<N>(v, par));
}
template <int N, class F>
__device__ __forceinline__ void validate(uint4* v, const uint4* p, F off, uint32_t par) {
    if (__builtin_expect(stale<N>(v, par), 0)) poll<N>(v, p, off, par);
}
__device__ __forceinline__ uint4 lds128(uint32_t a) {
    uint4 v;
    asm volatile("ld.shared.v4.u32 {%0,%1,%2,%3}, [%4];" : "=r"(v.x), "=r"(v.y), "=r"(v.z), "=r"(v.w) : "r"(a) : "memory");
    return v;
}
__device__ __forceinline__ uint32_t lds32(uint32_t a) {
    uint32_t v;
    asm volatile("ld.shared.u32 %0, [%1];" : "=r"(v) : "r"(a) : "memory");
    return v;
}
__device__ __forceinline__ void sts128(uint32_t a, uint32_t x, uint32_t y, uint32_t z, uint32_t w) {
    asm volatile("st.shared.v4.u32 [%0], {%1,%2,%3,%4};" ::"r"(a), "r"(x), "r"(y), "r"(z), "r"(w) : "memory");
}
__device__ __forceinline__ void stsm4(uint32_t a, uint32_t x, uint32_t y, uint32_t z, uint32_t w) {
    asm volatile("stmatrix.sync.aligned.m8n8.x4.shared.b16 [%0], {%1,%2,%3,%4};" ::"r"(a), "r"(x), "r"(y), "r"(z), "r"(w) : "memory");
}
__device__ __forceinline__ uint4 ldsm4(uint32_t a) {
    uint4 v;
    asm volatile("ldmatrix.sync.aligned.m8n8.x4.shared.b16 {%0,%1,%2,%3}, [%4];" : "=r"(v.x), "=r"(v.y), "=r"(v.z), "=r"(v.w) : "r"(a) : "memory");
    return v;
}
__device__ __forceinline__ uint4 ldsm4t(uint32_t a) {
    uint4 v;
    asm volatile("ldmatrix.sync.aligned.m8n8.x4.trans.shared.b16 {%0,%1,%2,%3}, [%4];" : "=r"(v.x), "=r"(v.y), "=r"(v.z), "=r"(v.w) : "r"(a) : "memory");
    return v;
}
template <int ACC, int NT = 2>
__device__ __forceinline__ void mma2(float* d, const uint4& a, const uint4& b) {
#pragma unroll
    for (int i = 0; i < NT; ++i)
        asm("mma.sync.aligned.m16n8k16.row.col.f32.bf16.bf16.f32 {%0,%1,%2,%3}, {%4,%5,%6,%7}, {%8,%9}, {%10,%11,%12,%13};"
            : "=f"(d[4 * i]), "=f"(d[4 * i + 1]), "=f"(d[4 * i + 2]), "=f"(d[4 * i + 3])
            : "r"(a.x), "r"(a.y), "r"(a.z), "r"(a.w), "r"(i ? b.z : b.x), "r"(i ? b.w : b.y), "f"(ACC ? d[4 * i] : 0.f),
              "f"(ACC ? d[4 * i + 1] : 0.f), "f"(ACC ? d[4 * i + 2] : 0.f), "f"(ACC ? d[4 * i + 3] : 0.f));
}
__device__ __forceinline__ uint32_t pack2(float lo, float hi) {
    uint32_t d;
    asm("cvt.rn.bf16x2.f32 %0, %1, %2;" : "=r"(d) : "f"(hi), "f"(lo));
    return d;
}
__device__ __forceinline__ uint4 pack8(const float* a) {
    return make_uint4(pack2(a[0], a[1]), pack2(a[2], a[3]), pack2(a[4], a[5]), pack2(a[6], a[7]));
}
__device__ __forceinline__ float bf_lo(uint32_t x) { return __uint_as_float(x << 16); }
__device__ __forceinline__ float bf_hi(uint32_t x) { return __uint_as_float(x & 0xffff0000u); }
__device__ __forceinline__ float u2f(uint32_t v) { return __uint_as_float(v); }
__device__ __forceinline__ uint32_t f2u(float v) { return __float_as_uint(v); }
__device__ __forceinline__ uint32_t hfma2(uint32_t a, uint32_t b, uint32_t c) {
    uint32_t d;
    asm("fma.rn.bf16x2 %0, %1, %2, %3;" : "=r"(d) : "r"(a), "r"(b), "r"(c));
    return d;
}
__device__ __forceinline__ uint32_t hmul2(uint32_t a, uint32_t b) {
    uint32_t d;
    asm("mul.rn.bf16x2 %0, %1, %2;" : "=r"(d) : "r"(a), "r"(b));
    return d;
}
__device__ __forceinline__ uint4 gate8(const float* a, const float* b) {
    const uint4 u = pack8(a), v = pack8(b);
    return make_uint4(hmul2(u.x, v.x), hmul2(u.y, v.y), hmul2(u.z, v.z), hmul2(u.w, v.w));
}
__device__ __forceinline__ float ex2f(float x) {
    float y;
    asm("ex2.approx.ftz.f32 %0, %1;" : "=f"(y) : "f"(x));
    return y;
}
__device__ __forceinline__ float rcpf(float x) {
    float y;
    asm("rcp.approx.ftz.f32 %0, %1;" : "=f"(y) : "f"(x));
    return y;
}
__device__ __forceinline__ float sqrtaf(float x) {
    float y;
    asm("sqrt.approx.ftz.f32 %0, %1;" : "=f"(y) : "f"(x));
    return y;
}
#define WG_FENCE() asm volatile("wgmma.fence.sync.aligned;" ::: "memory")
#define WG_COMMIT() asm volatile("wgmma.commit_group.sync.aligned;" ::: "memory")
#define WG_WAIT(n) asm volatile("wgmma.wait_group.sync.aligned %0;" ::"n"(n) : "memory")
template <int N>
__device__ __forceinline__ void pin(float* d) {
#pragma unroll
    for (int i = 0; i < N; ++i) asm volatile("" : "+f"(d[i])::"memory");
}

__device__ __forceinline__ uint64_t bdesc(uint32_t addr) {
    return (uint64_t)((addr >> 4) | (512u << 16)) | ((uint64_t)(64u | (1u << 30)) << 32);
}
__device__ __forceinline__ uint64_t cdesc(uint32_t addr, uint32_t lbo, uint32_t sbo) {
    return (uint64_t)((addr >> 4) | ((lbo >> 4) << 16)) | ((uint64_t)(sbo >> 4) << 32);
}
template <int SC>
__device__ __forceinline__ void wgmma128(float* d, const uint4& a, uint64_t db) {
    asm volatile("wgmma.mma_async.sync.aligned.m64n128k16.f32.bf16.bf16 {%0,%1,%2,%3,%4,%5,%6,%7,%8,%9,%10,%11,%12,%13,%14,%15,%16,%17,%18,%19,%20,%21,%22,%23,%24,%25,%26,%27,%28,%29,%30,%31,%32,%33,%34,%35,%36,%37,%38,%39,%40,%41,%42,%43,%44,%45,%46,%47,%48,%49,%50,%51,%52,%53,%54,%55,%56,%57,%58,%59,%60,%61,%62,%63}, "
                 "{%64,%65,%66,%67}, %68, %69, 1, 1, 1;"
                 : "+f"(d[0]), "+f"(d[1]), "+f"(d[2]), "+f"(d[3]), "+f"(d[4]), "+f"(d[5]), "+f"(d[6]), "+f"(d[7]), "+f"(d[8]), "+f"(d[9]), "+f"(d[10]), "+f"(d[11]), "+f"(d[12]), "+f"(d[13]), "+f"(d[14]), "+f"(d[15]), "+f"(d[16]), "+f"(d[17]), "+f"(d[18]), "+f"(d[19]), "+f"(d[20]), "+f"(d[21]), "+f"(d[22]), "+f"(d[23]), "+f"(d[24]), "+f"(d[25]), "+f"(d[26]), "+f"(d[27]), "+f"(d[28]), "+f"(d[29]), "+f"(d[30]), "+f"(d[31]), "+f"(d[32]), "+f"(d[33]), "+f"(d[34]), "+f"(d[35]), "+f"(d[36]), "+f"(d[37]), "+f"(d[38]), "+f"(d[39]), "+f"(d[40]), "+f"(d[41]), "+f"(d[42]), "+f"(d[43]), "+f"(d[44]), "+f"(d[45]), "+f"(d[46]), "+f"(d[47]), "+f"(d[48]), "+f"(d[49]), "+f"(d[50]), "+f"(d[51]), "+f"(d[52]), "+f"(d[53]), "+f"(d[54]), "+f"(d[55]), "+f"(d[56]), "+f"(d[57]), "+f"(d[58]), "+f"(d[59]), "+f"(d[60]), "+f"(d[61]), "+f"(d[62]), "+f"(d[63])
                 : "r"(a.x), "r"(a.y), "r"(a.z), "r"(a.w), "l"(db), "n"(SC));
}
template <int SC>
__device__ __forceinline__ void wgmma64(float* d, const uint4& a, uint64_t db) {
    asm volatile("wgmma.mma_async.sync.aligned.m64n64k16.f32.bf16.bf16 {%0,%1,%2,%3,%4,%5,%6,%7,%8,%9,%10,%11,%12,%13,%14,%15,%16,%17,%18,%19,%20,%21,%22,%23,%24,%25,%26,%27,%28,%29,%30,%31}, "
                 "{%32,%33,%34,%35}, %36, %37, 1, 1, 1;"
                 : "+f"(d[0]), "+f"(d[1]), "+f"(d[2]), "+f"(d[3]), "+f"(d[4]), "+f"(d[5]), "+f"(d[6]), "+f"(d[7]), "+f"(d[8]), "+f"(d[9]), "+f"(d[10]), "+f"(d[11]), "+f"(d[12]), "+f"(d[13]), "+f"(d[14]), "+f"(d[15]), "+f"(d[16]), "+f"(d[17]), "+f"(d[18]), "+f"(d[19]), "+f"(d[20]), "+f"(d[21]), "+f"(d[22]), "+f"(d[23]), "+f"(d[24]), "+f"(d[25]), "+f"(d[26]), "+f"(d[27]), "+f"(d[28]), "+f"(d[29]), "+f"(d[30]), "+f"(d[31])
                 : "r"(a.x), "r"(a.y), "r"(a.z), "r"(a.w), "l"(db), "n"(SC));
}
template <int SC>
__device__ __forceinline__ void wgmma48(float* d, const uint4& a, uint64_t db) {
    asm volatile("wgmma.mma_async.sync.aligned.m64n48k16.f32.bf16.bf16 {%0,%1,%2,%3,%4,%5,%6,%7,%8,%9,%10,%11,%12,%13,%14,%15,%16,%17,%18,%19,%20,%21,%22,%23}, "
                 "{%24,%25,%26,%27}, %28, %29, 1, 1, 1;"
                 : "+f"(d[0]), "+f"(d[1]), "+f"(d[2]), "+f"(d[3]), "+f"(d[4]), "+f"(d[5]), "+f"(d[6]), "+f"(d[7]), "+f"(d[8]), "+f"(d[9]), "+f"(d[10]), "+f"(d[11]), "+f"(d[12]), "+f"(d[13]), "+f"(d[14]), "+f"(d[15]), "+f"(d[16]), "+f"(d[17]), "+f"(d[18]), "+f"(d[19]), "+f"(d[20]), "+f"(d[21]), "+f"(d[22]), "+f"(d[23])
                 : "r"(a.x), "r"(a.y), "r"(a.z), "r"(a.w), "l"(db), "n"(SC));
}
template <int SC>
__device__ __forceinline__ void wgmma16(float* d, const uint4& a, uint64_t db) {
    asm volatile("wgmma.mma_async.sync.aligned.m64n16k16.f32.bf16.bf16 {%0,%1,%2,%3,%4,%5,%6,%7}, "
                 "{%8,%9,%10,%11}, %12, %13, 1, 1, 1;"
                 : "+f"(d[0]), "+f"(d[1]), "+f"(d[2]), "+f"(d[3]), "+f"(d[4]), "+f"(d[5]), "+f"(d[6]), "+f"(d[7])
                 : "r"(a.x), "r"(a.y), "r"(a.z), "r"(a.w), "l"(db), "n"(SC));
}

struct LnC { uint32_t rs0, nm0, rs1, nm1; };
__device__ __forceinline__ void ln_mod(uint4& a, uint4 cs, const LnC& c) {
    a.x = hfma2(hfma2(a.x, c.rs0, c.nm0), cs.x, cs.z);
    a.y = hfma2(hfma2(a.y, c.rs1, c.nm1), cs.x, cs.z);
    a.z = hfma2(hfma2(a.z, c.rs0, c.nm0), cs.y, cs.w);
    a.w = hfma2(hfma2(a.w, c.rs1, c.nm1), cs.y, cs.w);
}
__device__ __forceinline__ float rbf(float v) { return bf_lo(pack2(v, v)); }
__device__ __forceinline__ float silu_bf(float c) {
    float s = c * rcpf(1.0f + ex2f(c * -1.4426950408889634f));
    return rbf(s);
}
__device__ __forceinline__ void fma8(float* a, float s, uint4 w) {
    a[0] = fmaf(s, bf_lo(w.x), a[0]); a[1] = fmaf(s, bf_hi(w.x), a[1]);
    a[2] = fmaf(s, bf_lo(w.y), a[2]); a[3] = fmaf(s, bf_hi(w.y), a[3]);
    a[4] = fmaf(s, bf_lo(w.z), a[4]); a[5] = fmaf(s, bf_hi(w.z), a[5]);
    a[6] = fmaf(s, bf_lo(w.w), a[6]); a[7] = fmaf(s, bf_hi(w.w), a[7]);
}
__device__ __forceinline__ void red8(float* a, int lane) {
    const bool u16 = lane & 16, u8 = lane & 8, u4 = lane & 4;
#pragma unroll
    for (int k = 0; k < 4; ++k) {
        float keep = u16 ? a[k + 4] : a[k], send = u16 ? a[k] : a[k + 4];
        a[k] = keep + __shfl_xor_sync(~0u, send, 16);
    }
#pragma unroll
    for (int k = 0; k < 2; ++k) {
        float keep = u8 ? a[k + 2] : a[k], send = u8 ? a[k] : a[k + 2];
        a[k] = keep + __shfl_xor_sync(~0u, send, 8);
    }
    float keep = u4 ? a[1] : a[0], send = u4 ? a[0] : a[1];
    a[0] = keep + __shfl_xor_sync(~0u, send, 4);
    a[0] += __shfl_xor_sync(~0u, a[0], 2);
}
__device__ __forceinline__ void sumsq(uint32_t v, float& s, float& q) {
    const float a = bf_lo(v), b = bf_hi(v);
    s += a + b;
    q = fmaf(a, a, fmaf(b, b, q));
}
__device__ __forceinline__ void row_stats(float s, float q, uint32_t& rs, uint32_t& nm) {
    const float mean = s * (1.f / 512.f);
    const float var = rbf(rbf(fmaxf(fmaf(-mean, mean, q * (1.f / 512.f)), 0.f)) + 1e-5f);
    const float inv = rcpf(rbf(sqrtaf(var)));
    rs = pack2(inv, inv);
    const float m = -rbf(mean) * bf_lo(rs);
    nm = pack2(m, m);
}
__device__ __forceinline__ uint32_t one_plus(uint32_t v) { return pack2(1.0f + bf_lo(v), 1.0f + bf_hi(v)); }
__device__ __forceinline__ uint4 exp_pack(const float* s) {
    return make_uint4(pack2(ex2f(s[0]), ex2f(s[1])), pack2(ex2f(s[2]), ex2f(s[3])), pack2(ex2f(s[4]), ex2f(s[5])),
                      pack2(ex2f(s[6]), ex2f(s[7])));
}
template <int NB>
__device__ __forceinline__ void maxb(const float* s, float& m0, float& m1) {
#pragma unroll
    for (int i = 0; i < NB; ++i) {
        m0 = fmaxf(m0, fmaxf(fmaxf(s[8 * i], s[8 * i + 1]), fmaxf(s[8 * i + 4], s[8 * i + 5])));
        m1 = fmaxf(m1, fmaxf(fmaxf(s[8 * i + 2], s[8 * i + 3]), fmaxf(s[8 * i + 6], s[8 * i + 7])));
    }
}

struct Maps { CUtensorMap m[6]; };

__global__ void __launch_bounds__(384, 1)
fused_kernel(const __nv_bfloat16* __restrict__ x, const __nv_bfloat16* __restrict__ wqkv, const __nv_bfloat16* __restrict__ wo,
             const __nv_bfloat16* __restrict__ wg, const __nv_bfloat16* __restrict__ wu, const __nv_bfloat16* __restrict__ wd,
             const __nv_bfloat16* __restrict__ cvec, const __nv_bfloat16* __restrict__ wmod, __nv_bfloat16* __restrict__ out,
             const __grid_constant__ Maps tm) {
    extern __shared__ __align__(1024) unsigned char smem[];
    constexpr uint32_t sb = 1024;
    constexpr uint32_t bars = sb + BAR_OFF;
    const int bid = blockIdx.x;
    const int j = bid >> 3, r = bid & 7;
    const int lane = threadIdx.x & 31;
    const int warp = __shfl_sync(~0u, threadIdx.x >> 5, 0);
#define RELEASE(s0, n) do { _Pragma("unroll") for (int q_ = 0; q_ < (n); ++q_) mbar_arrive1(bars + 8 * (B_EMPTY + (s0) + q_)); } while (0)

    if (warp == 8) {
        if (elect()) {
            mbar_init(bars + 8 * B_XF, 1);
            mbar_init(bars + 8 * B_XF + 8, 1);
            mbar_expect(bars + 8 * B_XF, 4 * STAGE_BYTES);
            mbar_expect(bars + 8 * B_XF + 8, 4 * STAGE_BYTES);
#pragma unroll 1
            for (int n = 0; n < 8; ++n) tma2d(sb + (3 + n) * STAGE_BYTES, &tm.m[0], 64 * n, 128 * j, bars + 8 * (B_XF + (n >> 2)));
            PROF(1);
            if (s2u(smem) != sb) DIE();
#pragma unroll 1
            for (int i = 0; i < B_XF; i += 2) { mbar_init(bars + 8 * i, i < B_EMPTY ? 1 : 8); mbar_init(bars + 8 * i + 8, i < B_EMPTY ? 1 : 8); }
        }
        __syncwarp();
        bar_arrive(0, 288);
    }
    volatile unsigned* s_epoch = (volatile unsigned*)(smem + MISC_OFF);

    if (warp < 8) {
        const int w = warp, g = lane >> 2, t = lane & 3;
        const int row0 = 128 * j + 16 * w + g;
        uint4 A[32];
        LnC ln;
#define DB0(z) bdesc(sb + (z) * 16)
        uint32_t par;
        uint4 x1k;
        uint4* xb = g_x + (size_t)(j * 8 + w) * (X_ROWS * 32) + lane;
        asm volatile("mov.b64 %0, %0;" : "+l"(xb));
#define XROW(row) (xb + (row) * 32)
#define XR2(rt, row) (xb + (rt) * 32 + (row) * 32)
        {
            const unsigned epoch = (ld_u32(&g_cnt) >> 7) + 1;
            const int mrow = 256 * (bid & 1) + (threadIdx.x >> 1) * 2;
            const __nv_bfloat16* wp = wmod + (size_t)mrow * 3072 + 16 * (bid >> 1) + 8 * (lane & 1);
            const uint4 wv0 = ldg_nc(wp), wv1 = ldg_nc(wp + 3072);
            const uint32_t cv = __ldg((const uint32_t*)(cvec + mrow));
            const int srow = 128 * j + 16 * r + 2 * w + (lane >> 4);
            uint4 xs[4];
#pragma unroll
            for (int i = 0; i < 4; ++i) xs[i] = ldg_nc((const uint4*)x + (size_t)srow * 64 + i * 16 + (lane & 15));
            if ((lane & 15) == 0) st_rlx(&g_rs[srow], ~epoch, 0, 0, 0);
            if (threadIdx.x < 4) st_rlx(&g_m1[bid * 4 + lane], ~epoch, 0, 0, 0);
            float a[8];
#pragma unroll
            for (int k = 0; k < 8; ++k) a[k] = 0.f;
            fma8(a, silu_bf(bf_lo(cv)), wv0);
            fma8(a, silu_bf(bf_hi(cv)), wv1);
            red8(a, lane);
            float* red = (float*)(smem + RED_OFF);
            if ((lane & 2) == 0) red[w * 16 + (lane & 1) * 8 + (lane >> 2)] = a[0];
            float sm = 0.f, sq = 0.f;
#pragma unroll
            for (int i = 0; i < 4; ++i) { sumsq(xs[i].x, sm, sq); sumsq(xs[i].y, sm, sq); sumsq(xs[i].z, sm, sq); sumsq(xs[i].w, sm, sq); }
#pragma unroll
            for (int o = 1; o < 16; o <<= 1) { sm += __shfl_xor_sync(~0u, sm, o); sq += __shfl_xor_sync(~0u, sq, o); }
            uint32_t rs, nm;
            row_stats(sm, sq, rs, nm);
            PROF(16);
            par = epoch & 1u;
            *s_epoch = epoch;
            bar_sync(0, 288);
            if (threadIdx.x == 64) asm volatile("red.relaxed.gpu.global.add.u32 [%0], 1;" ::"l"(&g_cnt) : "memory");
            if (w == 1 && elect()) prefetch_l2((const char*)wqkv + bid * 12288, 12288);
            if ((lane & 15) == 0) st_rlx(&g_rs[srow], par, rs, nm, 0u);
            if (w == 0) {
                float4 v = *(const float4*)(red + 4 * lane);
#pragma unroll
                for (int o = 4; o < 32; o <<= 1) {
                    v.x += __shfl_xor_sync(~0u, v.x, o); v.y += __shfl_xor_sync(~0u, v.y, o);
                    v.z += __shfl_xor_sync(~0u, v.z, o); v.w += __shfl_xor_sync(~0u, v.w, o);
                }
                if (lane < 4) st_rlx(&g_m1[bid * 4 + lane], tagw(f2u(v.x), par), f2u(v.y), f2u(v.z), f2u(v.w));
            }
            PROF(0);
            asm volatile("setmaxnreg.inc.sync.aligned.u32 232;");
            uint4 pv[4];
            const uint4* mp = &g_m1[(threadIdx.x >> 2) * 8 + t];
            {
                const uint32_t xa = sb + 3 * STAGE_BYTES + (16 * w + (lane & 15)) * 128 + (((lane >> 4) ^ lane) & 7) * 16;
#pragma unroll
                for (int i = 0; i < 8; ++i) {
                    if ((i & 3) == 0) mbar_wait(bars + 8 * (B_XF + (i >> 2)), 0);
#pragma unroll
                    for (int c = 0; c < 4; ++c) A[4 * i + c] = ldsm4((xa ^ (c * 32)) + i * STAGE_BYTES);
                }
#pragma unroll
                for (int c = 0; c < 3; ++c) {
                    const uint4 v = ldsm4((xa ^ (c * 32)) + r * STAGE_BYTES);
                    sts128(sb + OUT_OFF + threadIdx.x * 16 + c * 4096, v.x, v.y, v.z, v.w);
                }
                x1k = ldsm4((xa ^ 96) + r * STAGE_BYTES);
            }
            PROF(15);
#pragma unroll 1
            do {
                pv[0] = ld_rlx(mp); pv[1] = ld_rlx(mp + 4);
                pv[2] = ld_rlx(&g_rs[row0]); pv[3] = ld_rlx(&g_rs[row0 + 8]);
            } while (stale<4>(pv, par));
            mbar_arrive1(bars + 8 * B_GO);
            const int i = threadIdx.x & 127;
            uint32_t v0 = pack2(u2f(pv[0].x) + u2f(pv[1].x), u2f(pv[0].y) + u2f(pv[1].y));
            uint32_t v1 = pack2(u2f(pv[0].z) + u2f(pv[1].z), u2f(pv[0].w) + u2f(pv[1].w));
            if (w >= 4) { v0 = one_plus(v0); v1 = one_plus(v1); }
            uint32_t* tp = (uint32_t*)(smem + TAB1_OFF) + (i >> 2) * 16 + (i & 1) * 8 + ((i >> 1) & 1) + (w >= 4 ? 0 : 2);
            tp[0] = v0; tp[4] = v1;
            ln.rs0 = pv[2].y; ln.nm0 = pv[2].z; ln.rs1 = pv[3].y; ln.nm1 = pv[3].z;
            bar_sync(1, 256);
        }
        PROF(1);

#pragma unroll 1
        for (int ph = 0; ph < 3; ++ph) {
            float acc[64];
            {
                const uint32_t tab = sb + (ph ? TAB2_OFF : TAB1_OFF) + t * 16;
                if (ph == 1) {
                    uint4 sv[2];
                    poll<2>(sv, XROW(X_ST) - lane + 16 * t + g, [](int i) { return 8 * i; }, par);
#pragma unroll
                    for (int i = 0; i < NB1; ++i) A[i] = ld_rlx(XROW(X_X1 + i));
                    float q0 = u2f(sv[0].x) + u2f(sv[1].x), s0 = u2f(sv[0].y) + u2f(sv[1].y);
                    float q1 = u2f(sv[0].z) + u2f(sv[1].z), s1 = u2f(sv[0].w) + u2f(sv[1].w);
#pragma unroll
                    for (int o = 1; o < 4; o <<= 1) {
                        s0 += __shfl_xor_sync(~0u, s0, o); q0 += __shfl_xor_sync(~0u, q0, o);
                        s1 += __shfl_xor_sync(~0u, s1, o); q1 += __shfl_xor_sync(~0u, q1, o);
                    }
                    row_stats(s0, q0, ln.rs0, ln.nm0);
                    row_stats(s1, q1, ln.rs1, ln.nm1);
                    validate<NB1>(A, XROW(X_X1), [](int i) { return 32 * i; }, par);
#pragma unroll
                    for (int i = NB1; i < 32; ++i) A[i] = ld_rlx(XROW(X_X1 + i));
                    bar_sync_if(w < 4, 4, 256);
                    PROF(7);
                }
                uint4 cs[4];
#pragma unroll
                for (int c = 0; c < 4; ++c) cs[c] = lds128(tab + c * 64);
#pragma unroll
                for (int i = 0; i < 8; ++i) {
                    const int slot = ph == 2 ? (8 + i) % NSTAGE : i, prev = ph == 2 ? (6 + i) % NSTAGE : i - 2;
                    if (4 * i == NB1 && ph == 1) validate<32 - NB1>(&A[NB1], XROW(X_X1 + NB1), [](int i) { return 32 * i; }, par);
                    if (ph < 2) {
#pragma unroll
                        for (int c = 0; c < 4; ++c) ln_mod(A[4 * i + c], cs[c], ln);
                        if (i < 7) {
#pragma unroll
                            for (int c = 0; c < 4; ++c) cs[c] = lds128(tab + (4 * i + 4 + c) * 64);
                        }
                    }
                    mbar_wait(bars + 8 * (B_FULL + slot), (i >= 3 && ph == 2) ? 1 : 0);
                    const uint64_t d = DB0(gridDim.z - 1) + slot * 1024;
                    WG_FENCE();
#pragma unroll
                    for (int c = 0; c < 4; ++c) {
                        if (i == 0 && c == 0) wgmma128<0>(acc, A[4 * i + c], d);
                        else wgmma128<1>(acc, A[4 * i + c], d + c * 128);
                    }
                    WG_COMMIT();
                    if (i > 1) {
                        WG_WAIT(2);
                        RELEASE(prev, 1);
                    }
                }
                WG_WAIT(0);
                pin<64>(acc);
                RELEASE(ph == 2 ? 3 : 6, 2);
            }
            if (ph) {
                uint4 hv[4];
#pragma unroll
                for (int c = 0; c < 4; ++c) { hv[c] = gate8(&acc[8 * c], &acc[32 + 8 * c]); hv[c].x = tagw(hv[c].x, par); }
#pragma unroll
                for (int c = 0; c < 4; ++c) st_rlx(XR2(r * 12 + 4 * ph, X_HH - 4 + c), hv[c].x, hv[c].y, hv[c].z, hv[c].w);
                PROF(7 + ph);
                continue;
            }
            PROF(2);
            uint4 qf, xr[4];
            const uint32_t qs = sb + OUT_OFF + threadIdx.x * 16;
            {
                const uint32_t kvw = sb + KV_OFF + (16 + w) * 1024 + ((lane >> 3) & 1) * 512 + (lane >> 4) * 128 + (lane & 7) * 16;
                const uint32_t km = t ? ~0u : ~1u, kp = t ? 0u : par;
#pragma unroll
                for (int q = 0; q < 8; ++q) {
                    const int i = (q >> 1) + 4 * (q & 1);
                    if (q == 0) mbar_wait(bars + 8 * (B_EMPTY + 2), 0);
                    if (q == 2) {
                        fence_async_smem();
                        __syncwarp();
                        if (j < 15 && elect()) {
                            bulk_s2g(g_kv + (size_t)bid * 2048 + w * 64, sb + KV_OFF + (16 + w) * 1024, 1024);
                            asm volatile("cp.async.bulk.commit_group;" ::: "memory");
                        }
                        mbar_wait(bars + 8 * (B_EMPTY + 6), 0);
                    }
                    const uint4 v = pack8(&acc[8 * i]);
                    stsm4(kvw + (i & 3) * 24576 + (i >> 2) * 256, (v.x & km) | kp, (v.y & km) | kp, (v.z & km) | kp, (v.w & km) | kp);
                }
                if (w < 3) {
                    const uint32_t id = (2 * t == g ? 0x3f80u : 0u) | (2 * t + 1 == g ? 0x3f800000u : 0u);
                    *(uint32_t*)(smem + ONES_OFF + threadIdx.x * 4) = (w & 1) ? 0u : id;
                }
                if (__builtin_expect(j < 2, 0)) {
#pragma unroll 1
                    for (int i = 0; i < 8 * (2 - j); ++i)
                        sts128(sb + KV_OFF + (i & 3) * 24576 + (i >> 2) * 4096 + threadIdx.x * 16, 0, 0, 0, 0);
                }
                fence_async_smem();
                __syncwarp();
                mbar_arrive1(bars + 8 * B_KVW);
                PROF(17);
                float accq[32];
#pragma unroll
                for (int q = 0; q < 4; ++q) {
                    const int slot = (8 + q) % NSTAGE;
                    mbar_wait(bars + 8 * (B_FULL + slot), q == 3 ? 1 : 0);
                    const uint64_t d = DB0(blockIdx.y) + slot * 1024;
                    WG_FENCE();
#pragma unroll
                    for (int s = 0; s < 8; ++s) {
                        if (q == 0 && s == 0) wgmma64<0>(accq, A[8 * q + s], d);
                        else wgmma64<1>(accq, A[8 * q + s], d + s * 128);
                    }
                }
                WG_COMMIT();
                WG_WAIT(0);
                pin<32>(accq);
                RELEASE(8, 3); RELEASE(0, 1);
#pragma unroll
                for (int i = 0; i < 32; ++i) accq[i] *= 0.25f * 1.4426950408889634f;
                qf = pack8(accq);
#pragma unroll
                for (int c = 0; c < 3; ++c) xr[c] = lds128(qs + c * 4096);
                xr[3] = x1k;
#pragma unroll
                for (int h = 1; h < 4; ++h) {
                    const uint4 v = pack8(&accq[8 * h]);
                    sts128(qs + (h - 1) * 4096, v.x, v.y, v.z, v.w);
                }
            }
            PROF(3);
            uint4* const st_own = XROW(X_ST) - lane + r * 8 + g;

            {
                const int wg = w >> 2, w4 = w & 3;
                const bool pC = 2 * t <= g, pD = 2 * t + 1 <= g;
                const uint32_t mD = (pC ? 0xffffu : 0u) | (pD ? 0xffff0000u : 0u);
                const uint32_t lk = sb + KV_OFF + w4 * 1024 + (lane >> 4) * 512 + ((lane >> 3) & 1) * 128 + (lane & 7) * 16;
                const uint32_t lv = sb + KV_OFF + w4 * 1024 + ((lane >> 3) & 1) * 512 + (lane >> 4) * 128 + (lane & 7) * 16 + 256;
                st_rlx(XR2(4 * r, X_O + 2), par ^ 1u, 0, 0, 0);
                st_rlx(XR2(4 * r, X_O + 3), par ^ 1u, 0, 0, 0);
                if (t == 0) st_rlx(st_own, par ^ 1u, 0, 0, 0);
                asm volatile("cp.async.bulk.wait_group.read 0;" ::: "memory");
                bar_sync(1, 256);
                bar_sync_if(wg == 0, 2, 256);
                uint32_t units = wg ? UNITS1 : UNITS0;
                int again = 0;
#pragma unroll 1
                while (true) {
                    const int h = units & 3, hf = (units >> 2) & 1;
                    const int b0 = 16 - 8 * j - 4 * hf - w4;
                    const uint32_t ka = lk + h * 24576 + hf * 4096, va = lv + h * 24576 + hf * 4096;
                    const uint4 qn = lds128(qs + (((units >> 4) & 3) - 1) * 4096 + (((units >> 6) & 1) - wg) * 2048);
                    mbar_wait(bars + 8 * (h ? B_HALO + h : B_HLD), 0);
                    if (h == 0) PROF(18);
                    float O[8], L[4];
#pragma unroll
                    for (int b = 1; b < 16; ++b) {
                        float S[8];
                        mma2<0>(S, qf, ldsm4(ka + b * 1024));
                        const uint4 P = exp_pack(S);
                        const uint32_t on = b < b0 ? 0u : 0x3f803f80u;
                        if (b == 1) { mma2<0>(O, P, ldsm4t(va + b * 1024)); mma2<0, 1>(L, P, make_uint4(on, on, 0u, 0u)); }
                        else { mma2<1>(O, P, ldsm4t(va + b * 1024)); mma2<1, 1>(L, P, make_uint4(on, on, 0u, 0u)); }
                        if (b == 8) {
                            float N[8];
                            mma2<0>(S, qf, ldsm4(ka + 16384));
                            mma2<0>(N, qf, ldsm4(ka));
                            S[0] = pC ? S[0] : N[0]; S[1] = pD ? S[1] : N[1]; S[4] = N[4]; S[5] = N[5];
                            S[6] = pC ? S[6] : N[6]; S[7] = pD ? S[7] : N[7];
                            const uint4 Q = exp_pack(S);
                            const uint4 Po = make_uint4(Q.x & ~mD, 0u, Q.z, Q.w & ~mD), Pn = make_uint4(Q.x & mD, Q.y, 0u, Q.w & mD);
                            const uint32_t o0 = b0 > 0 ? 0u : 0x3f803f80u;
                            mma2<1>(O, Pn, ldsm4t(va + 16384));
                            mma2<1, 1>(L, Pn, make_uint4(0x3f803f80u, 0x3f803f80u, 0u, 0u));
                            mma2<1>(O, Po, ldsm4t(va));
                            mma2<1, 1>(L, Po, make_uint4(o0, o0, 0u, 0u));
                            bar_arrive_if((units & 7) + 8 * again == 4, 2, 256);
                        }
                    }
                    if (__builtin_expect(__any_sync(~0u, (f2u(L[0]) >> 23) - 79u > 96u || (f2u(L[2]) >> 23) - 79u > 96u), 0)) {
                        float m0 = -3e38f, m1 = -3e38f;
#pragma unroll 1
                        for (int pass = 0; pass < 2; ++pass) {
#pragma unroll
                            for (int i = 0; i < 8; ++i) O[i] = 0.f;
#pragma unroll
                            for (int i = 0; i < 4; ++i) L[i] = 0.f;
#pragma unroll 1
                            for (int b = max(b0, 0); b <= 16; ++b) {
                                float S[8];
                                mma2<0>(S, qf, ldsm4(ka + b * 1024));
                                const bool dg = b == 16, od = b == 0;
                                if ((dg && !pC) || (od && pC)) S[0] = S[6] = -3e38f;
                                if ((dg && !pD) || (od && pD)) S[1] = S[7] = -3e38f;
                                if (od) S[2] = S[3] = -3e38f;
                                if (dg) S[4] = S[5] = -3e38f;
                                if (pass == 0) { maxb<1>(S, m0, m1); continue; }
#pragma unroll
                                for (int i = 0; i < 8; ++i) S[i] -= (i & 2) ? m1 : m0;
                                const uint4 P = exp_pack(S);
                                mma2<1>(O, P, ldsm4t(va + b * 1024));
                                mma2<1, 1>(L, P, make_uint4(0x3f803f80u, 0x3f803f80u, 0u, 0u));
                            }
#pragma unroll
                            for (int o = 1; o < 4; o <<= 1) { m0 = fmaxf(m0, __shfl_xor_sync(~0u, m0, o)); m1 = fmaxf(m1, __shfl_xor_sync(~0u, m1, o)); }
                        }
                    }
                    if (h == 0) {
                        mbar_wait(bars + 8 * B_HALO, 0);
                        if (__builtin_expect(((volatile unsigned char*)smem)[MISC_OFF + 4] > again, 0)) { again = 1; continue; }
                    }
                    const float i0 = rcpf(L[0]), i1 = rcpf(L[2]);
                    st_rlx(XR2(4 * r + h + (hf - wg) * 4 * X_ROWS, X_O), tagw(pack2(O[0] * i0, O[1] * i0), par), pack2(O[2] * i1, O[3] * i1),
                           pack2(O[4] * i0, O[5] * i0), pack2(O[6] * i1, O[7] * i1));
                    mbar_arrive_lt(bars + 8 * (B_EMPTY + 1 + h + (h >> 1) + lane), lane, h < 3 ? 1 + (h & 1) : 0);
                    qf = qn;
                    units = __shfl_sync(~0u, units >> 4, 0);
                    if (units < 16) break;
                    PROF(19 + (h > 2 ? 2 : h));
                }
            }
            PROF(4);

            {
                float acc[32];
#pragma unroll 1
                for (int m = 0; m < 4; ++m) mbar_wait(bars + 8 * (B_FULL + 7 + m), 1);
                const uint64_t d0 = DB0(blockIdx.z) + 7 * 1024;
#pragma unroll
                for (int h = 0; h < 4; ++h) {
                    if ((h & 1) == 0) {
                        poll<16>(&A[8 * h], XROW(X_O + h), [](int i) { return 128 * (i & 7) + 32 * (i >> 3); }, par);
                        WG_FENCE();
                    }
#pragma unroll
                    for (int i = 0; i < 8; ++i) {
                        if (h == 0 && i == 0) wgmma64<0>(acc, A[8 * h + i], d0);
                        else wgmma64<1>(acc, A[8 * h + i], d0 + i * 512 + h * 128);
                    }
                }
                WG_COMMIT();
                RELEASE(5, 2);
                if (w < 4) {
                    const int i = threadIdx.x;
                    uint4 v[3];
                    const int o2 = 16 * r + (lane < 16 ? lane : 368 + lane) - 128 - i;
                    poll<3>(v, &g_m2[128 + i], [&](int q) { return q < 2 ? 128 * q : o2; }, par);
                    uint32_t* tp = (uint32_t*)(smem + TAB2_OFF) + (i >> 2) * 16 + (i & 1) * 8 + ((i >> 1) & 1);
                    tp[2] = pack2(u2f(v[0].x), u2f(v[0].y)); tp[6] = pack2(u2f(v[0].z), u2f(v[0].w));
                    tp[0] = one_plus(pack2(u2f(v[1].x), u2f(v[1].y))); tp[4] = one_plus(pack2(u2f(v[1].z), u2f(v[1].w)));
                    *(float4*)(smem + GA_OFF + lane * 16) = make_float4(rbf(u2f(v[2].x)), rbf(u2f(v[2].y)), rbf(u2f(v[2].z)), rbf(u2f(v[2].w)));
                    __syncwarp();
                    mbar_arrive1(bars + 8 * B_TAB2);
                    mbar_arrive1(bars + 8 * B_TAB2);
                }
                mbar_wait(bars + 8 * B_TAB2, 0);
                WG_WAIT(0);
                pin<32>(acc);
                RELEASE(7, 4);
                bar_arrive_if(w >= 4, 4, 256);
                PROF(5);
                float s0 = 0.f, s1 = 0.f, q0 = 0.f, q1 = 0.f;
                uint32_t xo[16];
#pragma unroll
                for (int b = 0; b < 8; ++b) {
                    const float2 ga = *(const float2*)(smem + GA_OFF + (8 * b + 2 * t) * 4);
                    const uint32_t u0 = (b & 1) ? xr[b >> 1].z : xr[b >> 1].x, u1 = (b & 1) ? xr[b >> 1].w : xr[b >> 1].y;
                    const float v0 = fmaf(ga.x, acc[4 * b], bf_lo(u0)), v1 = fmaf(ga.y, acc[4 * b + 1], bf_hi(u0));
                    const float v2 = fmaf(ga.x, acc[4 * b + 2], bf_lo(u1)), v3 = fmaf(ga.y, acc[4 * b + 3], bf_hi(u1));
                    xo[2 * b] = pack2(v0, v1);
                    xo[2 * b + 1] = pack2(v2, v3);
                    s0 += v0 + v1; q0 = fmaf(v0, v0, fmaf(v1, v1, q0));
                    s1 += v2 + v3; q1 = fmaf(v2, v2, fmaf(v3, v3, q1));
                }
#pragma unroll
                for (int i = 0; i < 3; ++i) sts128(qs + i * 4096, xo[4 * i], xo[4 * i + 1], xo[4 * i + 2], xo[4 * i + 3]);
                x1k = make_uint4(xo[12], xo[13], xo[14], xo[15]);
#pragma unroll
                for (int i = 0; i < 4; ++i) xo[4 * i] = tagw(xo[4 * i], par);
#pragma unroll
                for (int i = 0; i < 4; ++i) st_rlx(XR2(4 * r, X_X1 + i), xo[4 * i], xo[4 * i + 1], xo[4 * i + 2], xo[4 * i + 3]);
#pragma unroll
                for (int o = 1; o < 4; o <<= 1) {
                    s0 += __shfl_xor_sync(~0u, s0, o); q0 += __shfl_xor_sync(~0u, q0, o);
                    s1 += __shfl_xor_sync(~0u, s1, o); q1 += __shfl_xor_sync(~0u, q1, o);
                }
                if (t == 0) st_rlx(st_own, tagw(f2u(q0), par), f2u(s0), f2u(q1), f2u(s1));
            }
            PROF(6);
            ln.rs0 = ln.nm0 = ln.rs1 = ln.nm1 = 0;
        }
        const uint4* const hp = XR2((r & 6) * 12, X_HH);
        auto off8 = [](int k) { return ((k >> 2) * 12 + (k & 3)) * 32; };
        {
            float ag[24], au[24];
#pragma unroll
            for (int i = 0; i < 8; ++i) {
                const int n = 38 + i;
                mbar_wait(bars + 8 * (B_FULL + n % NSTAGE), (n / NSTAGE) & 1);
                const uint64_t d = DB0(gridDim.y - 1) + (n % NSTAGE) * 1024;
                WG_FENCE();
#pragma unroll
                for (int c = 0; c < 4; ++c) {
                    if (i == 0 && c == 0) {
                        wgmma48<0>(ag, A[4 * i + c], d);
                        wgmma48<0>(au, A[4 * i + c], d + 512);
                    } else {
                        wgmma48<1>(ag, A[4 * i + c], d + c * 128);
                        wgmma48<1>(au, A[4 * i + c], d + 512 + c * 128);
                    }
                }
                WG_COMMIT();
                if (i < 3) st_rlx(XR2(r * 12, X_HH + 8 + i), par ^ 1u, 0, 0, 0);
                else if (i < 7) st_rlx(XR2(((r + 6) & 7) * 12, X_PT + 5 + i), par ^ 1u, 0, 0, 0);
                if (i > 0) {
                    WG_WAIT(1);
                    RELEASE((n - 1) % NSTAGE, 1);
                }
                if (i == 2 || i == 4) {
#pragma unroll
                    for (int c = 0; c < 8; ++c) A[4 * i - 8 + c] = ld_rlx(hp + 64 * (i - 2) + off8(c));
                }
            }
            WG_WAIT(0);
            pin<24>(ag); pin<24>(au);
            RELEASE(45 % NSTAGE, 1);
#pragma unroll
            for (int c = 0; c < 3; ++c) A[16 + c] = gate8(&ag[8 * c], &au[8 * c]);
        }
        PROF(10);
        {
            float acc[32];
            uint4 Q[12], X1[4];
#pragma unroll
            for (int c = 0; c < 3; ++c) {
                A[16 + c].x = tagw(A[16 + c].x, par);
                st_rlx(XR2(r * 12, X_HH + 8 + c), A[16 + c].x, A[16 + c].y, A[16 + c].z, A[16 + c].w);
            }
#pragma unroll
            for (int p = 0; p < 2; ++p) {
                mbar_wait(bars + 8 * (B_FULL + (46 + p) % NSTAGE), 0);
                if (p == 0) validate<16>(A, hp, [](int k) { return (((k >> 2) & 1) * 12 + (k & 3) + (k >> 3) * 4) * 32; }, par);
                const uint64_t d = DB0(blockDim.z - 1) + ((46 + p) % NSTAGE) * 1024;
                WG_FENCE();
#pragma unroll
                for (int k = 0; k < 8; ++k) {
                    if (p == 0 && k == 0) wgmma64<0>(acc, A[0], d);
                    else wgmma64<1>(acc, A[8 * p + k], d + k * 128);
                }
            }
            WG_COMMIT();
            WG_WAIT(0);
            pin<32>(acc);
            RELEASE(46 % NSTAGE, 1);
            int slot = 48 % NSTAGE, fpar = 0;
#pragma unroll 1
            for (int cb = 0; cb < 3; ++cb) {
                float af[32];
#pragma unroll
                for (int p = 0; p < 3; ++p) {
                    mbar_wait(bars + 8 * (B_FULL + slot), fpar);
                    if (p == 2 && cb == 0) poll<3>(&A[19], XR2((r ^ 1) * 12, X_HH + 8), [](int c) { return 32 * c; }, par);
                    const uint64_t d = DB0(blockDim.y - 1) + slot * 1024;
                    if (++slot == NSTAGE) { slot = 0; fpar = 1; }
                    WG_FENCE();
#pragma unroll
                    for (int k = 0; k < (p < 2 ? 8 : 6); ++k) {
                        if (p == 0 && k == 0) wgmma64<0>(af, A[k], d);
                        else if (p < 2) wgmma64<1>(af, A[8 * p + k], d + k * 128);
                        else wgmma64<1>(af, A[16 + k], d + ((k / 3) ^ (r & 1)) * 512 + (k % 3) * 128);
                    }
                }
                WG_COMMIT();
                WG_WAIT(0);
                pin<32>(af);
                uint4* dst = XR2(((r + 2 + 2 * cb) & 7) * 12 + 4 * cb, X_PT);
#pragma unroll
                for (int c = 0; c < 4; ++c) {
                    const uint4 v = pack8(&af[8 * c]);
                    st_rlx(dst + c * 32, tagw(v.x, par), v.y, v.z, v.w);
                }
            }
            {
                mbar_wait(bars + 8 * (B_FULL + 57 % NSTAGE), 1);
                const uint64_t d = DB0(gridDim.z - 1) + (57 % NSTAGE) * 1024;
                WG_FENCE();
#pragma unroll
                for (int k = 0; k < 6; ++k) wgmma64<1>(acc, A[16 + k], d + ((k / 3) ^ (r & 1)) * 512 + (k % 3) * 128);
                WG_COMMIT();
            }
            const uint64_t did = cdesc(sb + ONES_OFF + blockIdx.y * 16, 128, 128);
#pragma unroll
            for (int i = 0; i < 3; ++i) X1[i] = lds128(sb + OUT_OFF + threadIdx.x * 16 + i * 4096);
            X1[3] = x1k;
            PROF(11);
            poll<12>(Q, XR2(r * 12, X_PT), [](int i) { return 32 * i; }, par);
            float ap[4][8];
            WG_FENCE();
#pragma unroll
            for (int i = 0; i < 12; ++i) {
                if (i < 4) wgmma16<0>(ap[i], Q[i], did);
                else wgmma16<1>(ap[i & 3], Q[i], did);
            }
            WG_COMMIT();
            WG_WAIT(0);
            pin<32>(&ap[0][0]); pin<32>(acc);
            PROF(13);
            const uint32_t stg = sb + OUT_OFF + w * 512;
            uint32_t ln2;
            asm volatile("mov.u32 %0, %%laneid;" : "=r"(ln2));
            char* const op = (char*)out + (size_t)(128 * j + 16 * w) * 1024 + 128 * r + (ln2 >> 2) * 1024 + (ln2 & 3) * 16;
            __syncwarp();
#pragma unroll
            for (int hf = 0; hf < 2; ++hf) {
#pragma unroll
                for (int i = 2 * hf; i < 2 * hf + 2; ++i) {
                    const uint32_t xw[4] = {X1[i].x, X1[i].y, X1[i].z, X1[i].w};
                    uint32_t o[4];
#pragma unroll
                    for (int e = 0; e < 4; ++e) {
                        const float2 gb = *(const float2*)(smem + GB_OFF + (16 * i + 8 * (e >> 1) + 2 * t) * 4);
                        o[e] = pack2(fmaf(gb.x, acc[8 * i + 2 * e] + ap[i][2 * e], bf_lo(xw[e])),
                                     fmaf(gb.y, acc[8 * i + 2 * e + 1] + ap[i][2 * e + 1], bf_hi(xw[e])));
                    }
                    stsm4(stg + (lane & 8) * 512 + (lane & 7) * 64 + (((2 * (i & 1) + (lane >> 4)) ^ (lane >> 1)) & 3) * 16, o[0], o[1], o[2], o[3]);
                }
                __syncwarp();
#pragma unroll
                for (int k = 0; k < 2; ++k) {
                    const uint4 v = lds128(stg + k * 4096 + g * 64 + ((t ^ (g >> 1)) & 3) * 16);
                    *(uint4*)(op + k * 8192 + 64 * hf) = v;
                }
                __syncwarp();
            }
            mbar_arrive1(bars + 8 * B_DONE);
        }
        PROF(12);
        PROF_DUMP();
    } else {
        asm volatile("setmaxnreg.dec.sync.aligned.u32 40;");
        if (warp == 8) {
            uint4 tb[2];
            tb[0] = __ldg(&c_sched[lane]); tb[1] = __ldg(&c_sched[32 + lane]);
#pragma unroll
            for (int q = 0; q < 2; ++q) {
                const uint32_t c = ((tb[q].x & 0xffffu) + (tb[q].y & 255u) * r) & (tb[q].y >> 16);
                const uint32_t cr = c + (((tb[q].x >> 16) + ((tb[q].y >> 8) & 255u) * (r & 6)) << 16);
                if (q == 0 || lane < 26) sts128(sb + SCHED_OFF + q * 512 + lane * 16, cr, cr + tb[q].z, tb[q].w, 0);
            }
            __syncwarp();
            PROF(2);
            PROF_DUMP();
            bar_arrive(3, 128);
        } else {
            bar_sync(3, 128);
            mbar_wait(bars + 8 * B_GO, 0);
            const unsigned epoch = *s_epoch;
            if (warp < 11) {
                const int nn = j < 2 ? j : 2;
                const unsigned* fl = (const unsigned*)(g_kv + (size_t)(bid - 8 * ((lane >> 3) + 1)) * 2048 + (lane & 7) * 64 + 63);
                unsigned fv = epoch, fv2 = epoch;
                if (lane < 8 * nn) { fv = ld_u32(fl + (10 - warp) * 2048); fv2 = ld_u32(fl + (12 - warp) * 2048); }
                if (warp == 10 && elect()) {
                    prefetch_l2((const char*)wo + bid * 4096, 4096);
                    prefetch_l2((const char*)wg + bid * 11008, 11008);
                    prefetch_l2((const char*)wu + bid * 11008, 11008);
                    prefetch_l2((const char*)wd + bid * 11008, 11008);
                }
                mbar_wait(bars + 8 * (warp == 9 ? B_KVW : B_EMPTY + 5), 0);
                if (warp == 9 && elect()) {
                    if (j < 15) {
#pragma unroll 1
                        for (int h = 1; h < 4; ++h) {
                            if (h < 3) __nanosleep(PUBGAP);
                            bulk_s2g(g_kv + (size_t)bid * 2048 + h * 512, sb + KV_OFF + h * 24576 + 16384, 8192);
                        }
                        asm volatile("cp.async.bulk.commit_group;" ::: "memory");
                    }
                }
                PROF(1);
                uint32_t hb = 0, rph = 0;
#pragma unroll 1
                for (int h = 10 - warp; h < 4;) {
#pragma unroll 1
                    while ((fv ^ epoch) & 1u) fv = ld_u32(fl + h * 2048);
                    __syncwarp();
                    const uint32_t lb = hb ? hb : bars + 8 * (B_HLD + h);
                    if (elect()) {
                        mbar_expect(lb, nn * 8192);
#pragma unroll 1
                        for (int n = 1; n <= nn; ++n)
                            bulk_g2s(sb + KV_OFF + h * 24576 + (2 - n) * 8192, g_kv + (size_t)(bid - 8 * n) * 2048 + h * 512, 8192, lb);
                    }
                    mbar_wait(lb, hb ? rph : 0);
                    if (hb) rph ^= 1;
                    uint32_t bad = 0;
#pragma unroll 1
                    for (int n = 1; n <= nn; ++n) {
#pragma unroll
                        for (int i = 0; i < 16; ++i) bad |= lds32(sb + KV_OFF + h * 24576 + (2 - n) * 8192 + lane * 16 + i * 512) ^ epoch;
                    }
                    if (__any_sync(~0u, bad & 1u)) { hb = bars + 8 * (B_HRT + warp - 9); continue; }
                    smem[MISC_OFF + 4 + h] = hb != 0;
                    __syncwarp();
                    mbar_arrive1(bars + 8 * (B_HALO + h));
                    PROF(3 + h);
                    hb = 0;
                    h += 2;
                    fv = fv2;
                }
                if (warp == 9) {
                    asm volatile("cp.async.bulk.wait_group.read 0;" ::: "memory");
                    __syncwarp();
                    mbar_arrive1(bars + 8 * B_PUB);
                }
                PROF(2);
                PROF_DUMP();
            } else {
                const uint32_t par = epoch & 1u;
                if (lane < 4) prefetch_l2(wmod + (size_t)(4 * bid + lane) * 3072 + 1024, 4096);
                mbar_wait(bars + 8 * (B_FULL + 4), 0);
                {
                    const int half = lane & 1, rg = lane >> 1;
                    float a[8];
#pragma unroll
                    for (int k = 0; k < 8; ++k) a[k] = 0.f;
#pragma unroll 1
                    for (int b = 0; b < 8; ++b) {
                        const int row = b * 64 + rg * 4;
                        uint4 wv[4];
#pragma unroll
                        for (int i = 0; i < 4; ++i) wv[i] = ldg_nc(wmod + (size_t)(row + i) * 3072 + 1024 + 16 * bid + 8 * half);
                        const uint2 cv = *(const uint2*)(cvec + row);
                        fma8(a, silu_bf(bf_lo(cv.x)), wv[0]); fma8(a, silu_bf(bf_hi(cv.x)), wv[1]);
                        fma8(a, silu_bf(bf_lo(cv.y)), wv[2]); fma8(a, silu_bf(bf_hi(cv.y)), wv[3]);
                    }
                    red8(a, lane);
                    float* red2 = (float*)(smem + RED_OFF + 512);
                    if ((lane & 2) == 0) red2[half * 8 + (lane >> 2)] = a[0];
                    __syncwarp();
                    if (lane < 4) {
                        const uint4 v = *(const uint4*)(red2 + 4 * lane);
                        st_rlx(&g_m2[4 * bid + lane], tagw(v.x, par), v.y, v.z, v.w);
                    }
                    __syncwarp();
                }
                PROF(1);
                PROF(2);
                PROF_DUMP();
            }
        }
        if (warp < 11 && elect()) {
            uint32_t a = sb + SCHED_OFF + (warp == 8 ? 0 : (10 + warp) * 16);
            uint4 en = lds128(a);
#pragma unroll 1
            while (a < sb + SCHED_OFF + 58 * 16) {
                const uint4 e = en;
                a += a < sb + SCHED_OFF + 18 * 16 ? 16 : 48;
                en = lds128(a);
                const uint32_t slot = e.z & 15u, fb = bars + 8 * B_FULL + 8 * slot, dst = sb + slot * STAGE_BYTES;
                if (e.z & 0xff00u) mbar_wait_b(bars + ((e.z >> 5) & 0x7f8u), 0);
                mbar_wait_b(fb + 8 * (B_EMPTY - B_FULL), (e.z >> 5) & 1u);
                mbar_expect(fb, (e.z << 10) & STAGE_BYTES);
                if (e.z & 16u) {
                    tma2d(dst, &tm.m[(e.z >> 16) & 15u], e.x & 0xffffu, e.x >> 16, fb);
                    tma2d(dst + 8192, &tm.m[e.z >> 24], e.y & 0xffffu, e.y >> 16, fb);
                }
            }
            mbar_wait_b(bars + 8 * B_DONE, 0);
        }
    }
}

typedef CUresult (*EncodeFn)(CUtensorMap*, CUtensorMapDataType, cuuint32_t, void*, const cuuint64_t*, const cuuint64_t*,
                             const cuuint32_t*, const cuuint32_t*, CUtensorMapInterleave, CUtensorMapSwizzle,
                             CUtensorMapL2promotion, CUtensorMapFloatOOBfill);

void make2d(EncodeFn enc, CUtensorMap* m, const void* p, uint64_t cols, uint64_t rows, uint32_t box_rows = 64) {
    cuuint64_t dims[2] = {cols, rows};
    cuuint64_t str[1] = {cols * 2};
    cuuint32_t box[2] = {64, box_rows}, es[2] = {1, 1};
    enc(m, CU_TENSOR_MAP_DATA_TYPE_BFLOAT16, 2, (void*)p, dims, str, box, es, CU_TENSOR_MAP_INTERLEAVE_NONE,
        CU_TENSOR_MAP_SWIZZLE_128B, CU_TENSOR_MAP_L2_PROMOTION_L2_128B, CU_TENSOR_MAP_FLOAT_OOB_FILL_NONE);
}

}

extern "C" void kernel_launch(void* const* d_in, const int* in_sizes, int n_in, void* d_out, int out_size) {
    const __nv_bfloat16* x = (const __nv_bfloat16*)d_in[0];
    const __nv_bfloat16* wqkv = (const __nv_bfloat16*)d_in[1];
    const __nv_bfloat16* wo = (const __nv_bfloat16*)d_in[2];
    const __nv_bfloat16* wg = (const __nv_bfloat16*)d_in[4];
    const __nv_bfloat16* wu = (const __nv_bfloat16*)d_in[5];
    const __nv_bfloat16* wd = (const __nv_bfloat16*)d_in[6];
    const __nv_bfloat16* c = (const __nv_bfloat16*)d_in[7];
    const __nv_bfloat16* wmod = (const __nv_bfloat16*)d_in[8];

    void* fn = nullptr;
    cudaDriverEntryPointQueryResult qr;
    cudaGetDriverEntryPoint("cuTensorMapEncodeTiled", &fn, cudaEnableDefault, &qr);
    EncodeFn enc = (EncodeFn)fn;
    Maps tm;
    make2d(enc, &tm.m[0], x, 512, 2048, 128);
    make2d(enc, &tm.m[1], wqkv, 1536, 512);
    make2d(enc, &tm.m[2], wo, 512, 512);
    make2d(enc, &tm.m[3], wg, 1376, 512);
    make2d(enc, &tm.m[4], wu, 1376, 512);
    make2d(enc, &tm.m[5], wd, 512, 1376);
    cudaFuncSetAttribute(fused_kernel, cudaFuncAttributeMaxDynamicSharedMemorySize, SMEM_BYTES + PROF_EXTRA);
    fused_kernel<<<128, 384, SMEM_BYTES + PROF_EXTRA, cudaStreamPerThread>>>(x, wqkv, wo, wg, wu, wd, c, wmod, (__nv_bfloat16*)d_out, tm);
}
```
